```python
import torch

def _softmax(x, axis=-1):
    return torch.softmax(x, dim=axis)
def _gelu(x):
    return torch.nn.functional.gelu(x, approximate="tanh")
def _silu(x):
    return torch.nn.functional.silu(x)
def _sigmoid(x):
    return torch.sigmoid(x)
def _layernorm(x, axis=-1, eps=1e-5):
    m = x.mean(dim=axis, keepdim=True)
    v = x.var(dim=axis, keepdim=True, unbiased=False)
    return (x - m) / torch.sqrt(v + eps)
def _scatter_add(tgt, idx, src, axis=0):
    return tgt.clone().index_add_(axis, idx, src)
def _segment_sum(src, seg, n):
    out = torch.zeros((n,) + src.shape[1:], dtype=src.dtype)
    return out.index_add_(0, seg, src)
def _pad(x, pw):
    flat = tuple(v for pair in reversed(pw) for v in pair)
    return torch.nn.functional.pad(x, flat)

kernel_name = 'parallel_sum__sliding_block__glu_gated_glu__prompt'

def setup_inputs():

    _w = (lambda a: (lambda t: t.to(torch.bfloat16) if t.is_floating_point() else t)(torch.as_tensor(a)))
    def _A_setup():
        B, S, D = 1, 2048, 1024
        return {
            "x": _w((lambda *s: torch.randn(*s, dtype=torch.bfloat16) * 0.05)(B, S, D)),
            "wqkv": _w((lambda *s: torch.randn(*s, dtype=torch.bfloat16) * 0.05)(D, 3 * D)),
            "wo": _w((lambda *s: torch.randn(*s, dtype=torch.bfloat16) * 0.05)(D, D)),
        }
    _A_in = _A_setup()

    def _B_setup():
        B, S, D, F = 1, 2048, 1024, 3584
        return {
            "x": _w((lambda *s: torch.randn(*s, dtype=torch.bfloat16) * 0.05)(B, S, D)),
            "w_gate": _w((lambda *s: torch.randn(*s, dtype=torch.bfloat16) * 0.05)(D, F)),
            "w_up": _w((lambda *s: torch.randn(*s, dtype=torch.bfloat16) * 0.05)(D, F)),
            "w_down": _w((lambda *s: torch.randn(*s, dtype=torch.bfloat16) * 0.05)(F, D)),
        }
    _B_in = _B_setup()

    return {
        "A_x": _A_in["x"],
        "A_wqkv": _A_in["wqkv"],
        "A_wo": _A_in["wo"],
        "B_x": _B_in["x"],
        "B_w_gate": _B_in["w_gate"],
        "B_w_up": _B_in["w_up"],
        "B_w_down": _B_in["w_down"],
    }

def reference(A_x, A_wqkv, A_wo, B_x, B_w_gate, B_w_up, B_w_down):
    def _A_ref(x, wqkv, wo):
        B, S, D = x.shape
        H = 32; Dh = D // H; W = 256
        qkv = (lambda x, *d: x.permute(*d))((x @ wqkv).reshape(B, S, 3, H, Dh), 2, 0, 3, 1, 4)
        q, k, v = qkv[0], qkv[1], qkv[2]
        scores = torch.einsum("bhqd,bhkd->bhqk", q, k) * (Dh ** -0.5)
        idx = torch.arange(S)
        mask = (idx[:, None] - idx[None, :] >= 0) & (idx[:, None] - idx[None, :] < W)
        scores = torch.where(mask[None, None], scores, -1e9)
        p = _softmax(scores, axis=-1)
        o = torch.einsum("bhqk,bhkd->bhqd", p, v)
        return (lambda x, *d: x.permute(*d))(o, 0, 2, 1, 3).reshape(B, S, D) @ wo

    def _B_ref(x, w_gate, w_up, w_down):
        g = torch.einsum("bsd,df->bsf", x, w_gate)
        u = torch.einsum("bsd,df->bsf", x, w_up)
        h = _sigmoid(g) * u
        return torch.einsum("bsf,fd->bsd", h, w_down)

    x = A_x
    xn = _layernorm(x, axis=-1)
    return x + _A_ref(xn, A_wqkv, A_wo) + _B_ref(xn, B_w_gate, B_w_up, B_w_down)
```

```cpp
#include <cuda_runtime.h>
#include <cuda_bf16.h>
#include <cuda.h>
#include <stdint.h>
#include <stdio.h>

namespace fk {

constexpr int SEQ = 2048, DM = 1024, FF = 3584, KC = FF + DM;
constexpr int STAGES = 4;
constexpr int A_BYTES = 128 * 64 * 2, B_BYTES = 256 * 64 * 2, STAGE_BYTES = A_BYTES + B_BYTES;
constexpr int STG_OFF = STAGES * STAGE_BYTES;
constexpr int BAR_OFF = STG_OFF + 32768;
constexpr int SMEM_BYTES = BAR_OFF + 128;
constexpr int NCTA = 128, NTHREADS = 384;
constexpr int ATT_SEG = 4;
constexpr unsigned SPIN_LIMIT = 1u << 20;

struct Flags {
  unsigned ln[16 * 32];
  unsigned init[16 * 32];
  unsigned tile[16 * 64];
  unsigned done[32];
};

struct Maps {
  CUtensorMap xn, wqkv, wg, wu, wd, wo, kv_st, kv_ld, hc_st, hc_ld, out;
};

__device__ __align__(1024) __nv_bfloat16 g_xn[SEQ * DM];
__device__ __align__(1024) __nv_bfloat16 g_kv[SEQ * 2 * DM];
__device__ __align__(1024) __nv_bfloat16 g_hc[SEQ * KC];
__device__ __align__(1024) uint4 g_q[NCTA * 8 * 256];
__device__ __align__(1024) Flags g_flags;
__device__ volatile unsigned g_abort;

#define ACC8(d, i) "+f"(d[i]), "+f"(d[i + 1]), "+f"(d[i + 2]), "+f"(d[i + 3]), "+f"(d[i + 4]), "+f"(d[i + 5]), "+f"(d[i + 6]), "+f"(d[i + 7])
#define OUT8(d, i) "=f"(d[i]), "=f"(d[i + 1]), "=f"(d[i + 2]), "=f"(d[i + 3]), "=f"(d[i + 4]), "=f"(d[i + 5]), "=f"(d[i + 6]), "=f"(d[i + 7])
__device__ __forceinline__ void wgmma_rs_n256_z(float (&d)[128], uint32_t a0, uint32_t a1, uint32_t a2, uint32_t a3,
    uint32_t db) {
  asm volatile("{\n.reg .b64 db;\n"
    "mov.b64 db, {%132, 0x40000040};\n"
    "wgmma.mma_async.sync.aligned.m64n256k16.f32.bf16.bf16 {"
    "%0, %1, %2, %3, %4, %5, %6, %7, %8, %9, %10, %11, %12, %13, %14, %15, %16, %17, %18, %19, %20, %21, %22, %23, "
    "%24, %25, %26, %27, %28, %29, %30, %31, %32, %33, %34, %35, %36, %37, %38, %39, %40, %41, %42, %43, %44, %45, "
    "%46, %47, %48, %49, %50, %51, %52, %53, %54, %55, %56, %57, %58, %59, %60, %61, %62, %63, %64, %65, %66, %67, "
    "%68, %69, %70, %71, %72, %73, %74, %75, %76, %77, %78, %79, %80, %81, %82, %83, %84, %85, %86, %87, %88, %89, "
    "%90, %91, %92, %93, %94, %95, %96, %97, %98, %99, %100, %101, %102, %103, %104, %105, %106, %107, %108, %109, "
    "%110, %111, %112, %113, %114, %115, %116, %117, %118, %119, %120, %121, %122, %123, %124, %125, %126, %127"
    "}, {%128, %129, %130, %131}, db, 0, 1, 1, 0;\n}\n"
    : OUT8(d, 0), OUT8(d, 8), OUT8(d, 16), OUT8(d, 24), OUT8(d, 32), OUT8(d, 40), OUT8(d, 48), OUT8(d, 56), OUT8(d, 64), OUT8(d, 72), OUT8(d, 80), OUT8(d, 88), OUT8(d, 96), OUT8(d, 104), OUT8(d, 112), OUT8(d, 120)
    : "r"(a0), "r"(a1), "r"(a2), "r"(a3), "r"(db));
}

__device__ __forceinline__ void wgmma_rs_n64_z(float (&d)[32], uint32_t a0, uint32_t a1, uint32_t a2, uint32_t a3,
    uint32_t db) {
  asm volatile("{\n.reg .b64 db;\n"
    "mov.b64 db, {%36, 0x40000040};\n"
    "wgmma.mma_async.sync.aligned.m64n64k16.f32.bf16.bf16 {"
    "%0, %1, %2, %3, %4, %5, %6, %7, %8, %9, %10, %11, %12, %13, %14, %15, %16, %17, %18, %19, %20, %21, %22, %23, "
    "%24, %25, %26, %27, %28, %29, %30, %31"
    "}, {%32, %33, %34, %35}, db, 0, 1, 1, 0;\n}\n"
    : OUT8(d, 0), OUT8(d, 8), OUT8(d, 16), OUT8(d, 24)
    : "r"(a0), "r"(a1), "r"(a2), "r"(a3), "r"(db));
}

__device__ __forceinline__ void wgmma_rs_n32_tb_z(float (&d)[16], uint32_t a0, uint32_t a1, uint32_t a2, uint32_t a3,
    uint32_t db) {
  asm volatile("{\n.reg .b64 db;\n"
    "mov.b64 db, {%20, 0x40000040};\n"
    "wgmma.mma_async.sync.aligned.m64n32k16.f32.bf16.bf16 {"
    "%0, %1, %2, %3, %4, %5, %6, %7, %8, %9, %10, %11, %12, %13, %14, %15"
    "}, {%16, %17, %18, %19}, db, 0, 1, 1, 1;\n}\n"
    : OUT8(d, 0), OUT8(d, 8)
    : "r"(a0), "r"(a1), "r"(a2), "r"(a3), "r"(db));
}

__device__ __forceinline__ void wgmma_ss_n256_tb(float (&d)[128], uint32_t da, uint32_t db, int sd) {
  asm volatile("{\n.reg .pred p;\n.reg .b64 da, db;\nsetp.ne.b32 p, %130, 0;\n"
    "mov.b64 da, {%128, 0x40000040};\nmov.b64 db, {%129, 0x40000040};\n"
    "wgmma.mma_async.sync.aligned.m64n256k16.f32.bf16.bf16 {"
    "%0, %1, %2, %3, %4, %5, %6, %7, %8, %9, %10, %11, %12, %13, %14, %15, %16, %17, %18, %19, %20, %21, %22, %23, "
    "%24, %25, %26, %27, %28, %29, %30, %31, %32, %33, %34, %35, %36, %37, %38, %39, %40, %41, %42, %43, %44, %45, "
    "%46, %47, %48, %49, %50, %51, %52, %53, %54, %55, %56, %57, %58, %59, %60, %61, %62, %63, %64, %65, %66, %67, "
    "%68, %69, %70, %71, %72, %73, %74, %75, %76, %77, %78, %79, %80, %81, %82, %83, %84, %85, %86, %87, %88, %89, "
    "%90, %91, %92, %93, %94, %95, %96, %97, %98, %99, %100, %101, %102, %103, %104, %105, %106, %107, %108, %109, "
    "%110, %111, %112, %113, %114, %115, %116, %117, %118, %119, %120, %121, %122, %123, %124, %125, %126, %127"
    "}, da, db, p, 1, 1, 0, 1;\n}\n"
    : ACC8(d, 0), ACC8(d, 8), ACC8(d, 16), ACC8(d, 24), ACC8(d, 32), ACC8(d, 40), ACC8(d, 48), ACC8(d, 56), ACC8(d, 64), ACC8(d, 72), ACC8(d, 80), ACC8(d, 88), ACC8(d, 96), ACC8(d, 104), ACC8(d, 112), ACC8(d, 120)
    : "r"(da), "r"(db), "r"(sd));
}

__device__ __forceinline__ void wgmma_rs_n256(float (&d)[128], uint32_t a0, uint32_t a1, uint32_t a2, uint32_t a3,
    uint32_t db, int sd) {
  asm volatile("{\n.reg .pred p;\n.reg .b64 db;\nsetp.ne.b32 p, %133, 0;\n"
    "mov.b64 db, {%132, 0x40000040};\n"
    "wgmma.mma_async.sync.aligned.m64n256k16.f32.bf16.bf16 {"
    "%0, %1, %2, %3, %4, %5, %6, %7, %8, %9, %10, %11, %12, %13, %14, %15, %16, %17, %18, %19, %20, %21, %22, %23, "
    "%24, %25, %26, %27, %28, %29, %30, %31, %32, %33, %34, %35, %36, %37, %38, %39, %40, %41, %42, %43, %44, %45, "
    "%46, %47, %48, %49, %50, %51, %52, %53, %54, %55, %56, %57, %58, %59, %60, %61, %62, %63, %64, %65, %66, %67, "
    "%68, %69, %70, %71, %72, %73, %74, %75, %76, %77, %78, %79, %80, %81, %82, %83, %84, %85, %86, %87, %88, %89, "
    "%90, %91, %92, %93, %94, %95, %96, %97, %98, %99, %100, %101, %102, %103, %104, %105, %106, %107, %108, %109, "
    "%110, %111, %112, %113, %114, %115, %116, %117, %118, %119, %120, %121, %122, %123, %124, %125, %126, %127"
    "}, {%128, %129, %130, %131}, db, p, 1, 1, 0;\n}\n"
    : ACC8(d, 0), ACC8(d, 8), ACC8(d, 16), ACC8(d, 24), ACC8(d, 32), ACC8(d, 40), ACC8(d, 48), ACC8(d, 56), ACC8(d, 64), ACC8(d, 72), ACC8(d, 80), ACC8(d, 88), ACC8(d, 96), ACC8(d, 104), ACC8(d, 112), ACC8(d, 120)
    : "r"(a0), "r"(a1), "r"(a2), "r"(a3), "r"(db), "r"(sd));
}

__device__ __forceinline__ void wgmma_rs_n64(float (&d)[32], uint32_t a0, uint32_t a1, uint32_t a2, uint32_t a3,
    uint32_t db, int sd) {
  asm volatile("{\n.reg .pred p;\n.reg .b64 db;\nsetp.ne.b32 p, %37, 0;\n"
    "mov.b64 db, {%36, 0x40000040};\n"
    "wgmma.mma_async.sync.aligned.m64n64k16.f32.bf16.bf16 {"
    "%0, %1, %2, %3, %4, %5, %6, %7, %8, %9, %10, %11, %12, %13, %14, %15, %16, %17, %18, %19, %20, %21, %22, %23, "
    "%24, %25, %26, %27, %28, %29, %30, %31"
    "}, {%32, %33, %34, %35}, db, p, 1, 1, 0;\n}\n"
    : ACC8(d, 0), ACC8(d, 8), ACC8(d, 16), ACC8(d, 24)
    : "r"(a0), "r"(a1), "r"(a2), "r"(a3), "r"(db), "r"(sd));
}

__device__ __forceinline__ void wgmma_rs_n32_tb(float (&d)[16], uint32_t a0, uint32_t a1, uint32_t a2, uint32_t a3,
    uint32_t db, int sd) {
  asm volatile("{\n.reg .pred p;\n.reg .b64 db;\nsetp.ne.b32 p, %21, 0;\n"
    "mov.b64 db, {%20, 0x40000040};\n"
    "wgmma.mma_async.sync.aligned.m64n32k16.f32.bf16.bf16 {"
    "%0, %1, %2, %3, %4, %5, %6, %7, %8, %9, %10, %11, %12, %13, %14, %15"
    "}, {%16, %17, %18, %19}, db, p, 1, 1, 1;\n}\n"
    : ACC8(d, 0), ACC8(d, 8)
    : "r"(a0), "r"(a1), "r"(a2), "r"(a3), "r"(db), "r"(sd));
}

__device__ __forceinline__ void wg_fence() { asm volatile("wgmma.fence.sync.aligned;" ::: "memory"); }
__device__ __forceinline__ void wg_commit() { asm volatile("wgmma.commit_group.sync.aligned;" ::: "memory"); }
template <int N>
__device__ __forceinline__ void wg_wait() { asm volatile("wgmma.wait_group.sync.aligned %0;" ::"n"(N) : "memory"); }
template <int N>
__device__ __forceinline__ void pin(float (&d)[N]) {
#pragma unroll
  for (int i = 0; i < N; i++) asm volatile("" : "+f"(d[i])::"memory");
}
__device__ __forceinline__ void mbar_init(uint32_t bar, uint32_t cnt) {
  asm volatile("mbarrier.init.shared::cta.b64 [%0], %1;" ::"r"(bar), "r"(cnt) : "memory");
}
__device__ __forceinline__ bool mbar_try(uint32_t bar, uint32_t parity) {
  uint32_t ok;
  asm volatile(
      "{\n.reg .pred p;\nmbarrier.try_wait.parity.shared::cta.b64 p, [%1], %2;\nselp.u32 %0, 1, 0, p;\n}\n"
      : "=r"(ok)
      : "r"(bar), "r"(parity)
      : "memory");
  return ok != 0;
}
__device__ __forceinline__ bool give_up(unsigned& n) {
  if ((++n & 1023) != 0) return false;
  if (n >= SPIN_LIMIT) g_abort = 1;
  return g_abort != 0;
}
__device__ __forceinline__ void mbar_wait(uint32_t bar, uint32_t parity) {
  if (mbar_try(bar, parity)) return;
  unsigned n = 0;
  while (!mbar_try(bar, parity)) {
    if (give_up(n)) break;
  }
}
__device__ __forceinline__ void mbar_expect_tx(uint32_t bar, uint32_t bytes) {
  asm volatile("mbarrier.arrive.expect_tx.shared::cta.b64 _, [%0], %1;" ::"r"(bar), "r"(bytes) : "memory");
}
__device__ __forceinline__ void mbar_arrive_cluster(uint32_t addr) {
  asm volatile("mbarrier.arrive.shared::cluster.b64 _, [%0];" ::"r"(addr) : "memory");
}
__device__ __forceinline__ uint32_t mapa(uint32_t addr, uint32_t rank) {
  uint32_t r;
  asm("mapa.shared::cluster.u32 %0, %1, %2;" : "=r"(r) : "r"(addr), "r"(rank));
  return r;
}
__device__ __forceinline__ void tma_ld2(uint32_t dst, const CUtensorMap* m, int c0, int c1, uint32_t bar) {
  asm volatile(
      "cp.async.bulk.tensor.2d.shared::cluster.global.mbarrier::complete_tx::bytes [%0], [%1, {%3, %4}], [%2];" ::"r"(dst),
      "l"(m), "r"(bar), "r"(c0), "r"(c1)
      : "memory");
}
__device__ __forceinline__ void tma_ld3_mc(uint32_t dst, const CUtensorMap* m, int c1, int c2, uint32_t bar) {
  asm volatile(
      "cp.async.bulk.tensor.3d.shared::cluster.global.mbarrier::complete_tx::bytes.multicast::cluster "
      "[%0], [%1, {%3, %4, %5}], [%2], %6;" ::"r"(dst),
      "l"(m), "r"(bar), "r"(0), "r"(c1), "r"(c2), "h"((uint16_t)3)
      : "memory");
}
__device__ __forceinline__ void tma_ld3(uint32_t dst, const CUtensorMap* m, int c1, int c2, uint32_t bar) {
  asm volatile(
      "cp.async.bulk.tensor.3d.shared::cluster.global.mbarrier::complete_tx::bytes "
      "[%0], [%1, {%3, %4, %5}], [%2];" ::"r"(dst),
      "l"(m), "r"(bar), "r"(0), "r"(c1), "r"(c2)
      : "memory");
}
__device__ __forceinline__ void tma_st2(const CUtensorMap* m, int c0, int c1, uint32_t src) {
  asm volatile("cp.async.bulk.tensor.2d.global.shared::cta.bulk_group [%0, {%2, %3}], [%1];" ::"l"(m), "r"(src),
               "r"(c0), "r"(c1)
               : "memory");
}
__device__ __forceinline__ void tma_red2(const CUtensorMap* m, int c0, int c1, uint32_t src) {
  asm volatile("cp.reduce.async.bulk.tensor.2d.global.shared::cta.add.tile.bulk_group [%0, {%2, %3}], [%1];" ::"l"(m),
               "r"(src), "r"(c0), "r"(c1)
               : "memory");
}
__device__ __forceinline__ void bulk_commit() { asm volatile("cp.async.bulk.commit_group;" ::: "memory"); }
__device__ __forceinline__ void bulk_wait_all() { asm volatile("cp.async.bulk.wait_group 0;" ::: "memory"); }
__device__ __forceinline__ void bulk_wait_read() { asm volatile("cp.async.bulk.wait_group.read 0;" ::: "memory"); }
__device__ __forceinline__ void fence_async_smem() { asm volatile("fence.proxy.async.shared::cta;" ::: "memory"); }
__device__ __forceinline__ void fence_async_all() { asm volatile("fence.proxy.async;" ::: "memory"); }
__device__ __forceinline__ void named_bar(int id, int n) { asm volatile("bar.sync %0, %1;" ::"r"(id), "r"(n) : "memory"); }
__device__ __forceinline__ void named_arrive(int id, int n) {
  asm volatile("bar.arrive %0, %1;" ::"r"(id), "r"(n) : "memory");
}
__device__ __forceinline__ void cluster_arrive() { asm volatile("barrier.cluster.arrive.release.aligned;" ::: "memory"); }
__device__ __forceinline__ void cluster_wait() { asm volatile("barrier.cluster.wait.acquire.aligned;" ::: "memory"); }
__device__ __forceinline__ void flag_add(unsigned* p) {
  asm volatile("red.release.gpu.global.add.u32 [%0], 1;" ::"l"(p) : "memory");
}
__device__ __forceinline__ unsigned ld_acq(const unsigned* p) {
  unsigned v;
  asm volatile("ld.acquire.gpu.global.u32 %0, [%1];" : "=r"(v) : "l"(p) : "memory");
  return v;
}
__device__ __forceinline__ void warp_poll(const unsigned* p, unsigned want) {
  if (p) {
    unsigned n = 0;
    while (ld_acq(p) < want) {
      if (give_up(n)) break;
    }
  }
  __syncwarp();
  fence_async_all();
}
__device__ __forceinline__ void stsm4(uint32_t addr, uint32_t a, uint32_t b, uint32_t c, uint32_t d) {
  asm volatile("stmatrix.sync.aligned.m8n8.x4.shared.b16 [%0], {%1, %2, %3, %4};" ::"r"(addr), "r"(a), "r"(b), "r"(c),
               "r"(d)
               : "memory");
}
__device__ __forceinline__ uint32_t pack2(float lo, float hi) {
  uint32_t r;
  asm("cvt.rn.bf16x2.f32 %0, %1, %2;" : "=r"(r) : "f"(hi), "f"(lo));
  return r;
}
__device__ __forceinline__ float bf_lo(uint32_t v) { return __uint_as_float(v << 16); }
__device__ __forceinline__ float bf_hi(uint32_t v) { return __uint_as_float(v & 0xffff0000u); }
__device__ __forceinline__ float bf_round(float v) { return __bfloat162float(__float2bfloat16_rn(v)); }
__device__ __forceinline__ float ex2(float x) {
  float y;
  asm("ex2.approx.ftz.f32 %0, %1;" : "=f"(y) : "f"(x));
  return y;
}
__device__ __forceinline__ float rcp(float x) {
  float y;
  asm("rcp.approx.ftz.f32 %0, %1;" : "=f"(y) : "f"(x));
  return y;
}
__device__ __forceinline__ uint32_t make_desc(uint32_t addr, uint32_t lbo) { return (addr >> 4) | ((lbo >> 4) << 16); }
__device__ __forceinline__ void release_stage(uint32_t e0, uint32_t e1, int st, int lane) {
  if (lane == 0) {
    mbar_arrive_cluster(e0 + 8 * st);
    mbar_arrive_cluster(e1 + 8 * st);
  }
}
__device__ __forceinline__ uint32_t glu2(uint32_t g, uint32_t u) {
  constexpr float NL2E = -1.4426950408889634f;
  float s0 = rcp(1.0f + ex2(bf_lo(g) * NL2E));
  float s1 = rcp(1.0f + ex2(bf_hi(g) * NL2E));
  return pack2(s0 * bf_lo(u), s1 * bf_hi(u));
}
#define TS(slot) do { } while (0)
#define TSP(slot) do { } while (0)

enum { P_NONE = 0, P_QK = 1, P_V = 2, P_GU = 3 };

__device__ __forceinline__ int g2_ktile(int kh, int i) {
  return kh == 0 ? (i < 14 ? i : i + 6) : (i < 6 ? 14 + i : (i < 14 ? 22 + i : 10 + i));
}

constexpr int BAR_READY = 1, BAR_FREE = 3, BAR_LN = 5, BAR_WG = 6;

struct Epi {
  uint32_t sta;
  uint4* qptr;
  int w;
};
__device__ __forceinline__ void stage_full(const Epi& e) {
  fence_async_smem();
  named_arrive(BAR_READY + e.w, 160);
}

template <int S>
__device__ __forceinline__ void epi_chunk(int type, const uint32_t (&pk)[64], const Epi& e) {
  if (type == P_GU) {
    if (S == 0) named_bar(BAR_FREE + e.w, 160);
    if (S < 8) {
      uint32_t h0 = glu2(pk[(4 * S) & 31], pk[32 + ((4 * S) & 31)]);
      uint32_t h1 = glu2(pk[(4 * S + 1) & 31], pk[32 + ((4 * S + 1) & 31)]);
      uint32_t h2 = glu2(pk[(4 * S + 2) & 31], pk[32 + ((4 * S + 2) & 31)]);
      uint32_t h3 = glu2(pk[(4 * S + 3) & 31], pk[32 + ((4 * S + 3) & 31)]);
      stsm4((e.sta ^ ((S & 3) << 5)) + ((S & 7) >> 2) * 8192, h0, h1, h2, h3);
    }
    if (S == 7) stage_full(e);
  } else if (type == P_QK) {
    if (S < 8) {
      constexpr int I = S & 7;
      stsm4((e.sta ^ ((I & 3) << 5)) + (I >> 2) * 8192, pk[32 + 4 * I], pk[33 + 4 * I], pk[34 + 4 * I], pk[35 + 4 * I]);
      e.qptr[I * 256] = make_uint4(pk[4 * I], pk[4 * I + 1], pk[4 * I + 2], pk[4 * I + 3]);
    }
    if (S == 7) stage_full(e);
  } else if (type == P_V) {
    if (S == 0 || S == 6) named_bar(BAR_FREE + e.w, 160);
    if (S < 4 || (S >= 6 && S < 10)) {
      constexpr int H = S < 4 ? 0 : 1;
      constexpr int I0 = 2 * ((S < 4 ? S : S - 6) & 3);
#pragma unroll
      for (int i = I0; i < I0 + 2; i++)
        stsm4((e.sta ^ ((i & 3) << 5)) + (i >> 2) * 8192, pk[32 * H + 4 * i], pk[32 * H + 4 * i + 1],
              pk[32 * H + 4 * i + 2], pk[32 * H + 4 * i + 3]);
    }
    if (S == 3 || S == 9) stage_full(e);
  }
}

template <int S, int END, bool FRESH>
__device__ __forceinline__ void steps(float (&acc)[128], const uint32_t (&pk)[64], const Epi& e, int type, uint32_t fullb,
                                      uint32_t e0, uint32_t e1, uint32_t& ph, uint32_t da, uint32_t db, int lane) {
  constexpr int ST = S & 3;
  mbar_wait(fullb + 8 * ST, ph);
  wg_fence();
#pragma unroll
  for (int kk = 0; kk < 4; kk++)
    wgmma_ss_n256_tb(acc, da + (ST * (STAGE_BYTES >> 4) + kk * 2), db + (ST * (STAGE_BYTES >> 4) + kk * 128),
                     (FRESH && S == 0 && kk == 0) ? 0 : 1);
  wg_commit();
  if (S > 0 || !FRESH) {
    wg_wait<1>();
    release_stage(e0, e1, (S + 3) & 3, lane);
  }
  epi_chunk<S>(type, pk, e);
  if (ST == 3) ph ^= 1;
  if constexpr (S + 1 < END) steps<S + 1, END, FRESH>(acc, pk, e, type, fullb, e0, e1, ph, da, db, lane);
}
template <int S>
__device__ __forceinline__ void epi_drain(int type, const uint32_t (&pk)[64], const Epi& e) {
  epi_chunk<S>(type, pk, e);
  if constexpr (S < 7) epi_drain<S + 1>(type, pk, e);
}

__global__ void __cluster_dims__(2, 1, 1) __launch_bounds__(NTHREADS, 1)
    fused_kernel(const __grid_constant__ Maps maps, const __nv_bfloat16* __restrict__ x, __nv_bfloat16* __restrict__ out) {
  extern __shared__ __align__(1024) uint8_t smem[];
  const uint32_t sb = (uint32_t)__cvta_generic_to_shared(smem);
  const int tid = threadIdx.x, lane = tid & 31;
  const int warp = __shfl_sync(0xffffffffu, tid >> 5, 0);
  const int rank = blockIdx.x & 1, cl = blockIdx.x >> 1;
  const int m = 2 * (cl & 7) + rank, j = cl >> 3;
  const uint32_t fullb = sb + BAR_OFF, emptyb = fullb + 8 * STAGES;
  Flags* fl = &g_flags;

  if (tid == 0) {
#pragma unroll
    for (int s = 0; s < STAGES; s++) {
      mbar_init(fullb + 8 * s, 1);
      mbar_init(emptyb + 8 * s, 16);
    }
    asm volatile("fence.mbarrier_init.release.cluster;" ::: "memory");
  }
  __syncwarp();
  cluster_arrive();

  if (warp < 4) {
    asm volatile("setmaxnreg.dec.sync.aligned.u32 40;");
    cluster_wait();
    if (warp == 0) {
      TSP(0);
      uint32_t ph = 1;
      const int arow = m * 128;
      for (int wv = 0; wv < 5; wv++) {
        if (wv == ATT_SEG) {
          const unsigned* p = nullptr;
          if (lane < 6) {
            int mm = m - (lane % 3);
            if (mm >= 0) p = &fl->tile[mm * 64 + (lane < 3 ? j : 8 + (j >> 1))];
          }
          warp_poll(p, 2);
#pragma unroll 1
          for (int s = 0; s < 4; s++) {
            mbar_wait(emptyb + 8 * s, ph);
            if (lane == 0) {
              mbar_expect_tx(fullb + 8 * s, STAGE_BYTES);
              const int col = (s & 1) * 1024 + j * 128 + (s >> 1) * 64;
#pragma unroll
              for (int b = 0; b < 3; b++)
                tma_ld2(sb + s * STAGE_BYTES + b * 16384, &maps.kv_ld, col, arow - 256 + 128 * b, fullb + 8 * s);
            }
          }
          ph ^= 1;
        }
        const int n = 8 * wv + j;
        const CUtensorMap* bm;
        int bc;
        if (wv == 0) {
          bm = &maps.wqkv;
          bc = (rank * 1024 + j * 128) >> 6;
        } else if (n < 12) {
          bm = &maps.wqkv;
          bc = (2048 + j * 256 + rank * 128) >> 6;
        } else {
          bm = rank ? &maps.wu : &maps.wg;
          bc = (n - 12) * 2;
        }
        int ks = 0;
        if (wv == 0) {
          if (lane == 0) {
#pragma unroll
            for (int s = 0; s < 4; s++) {
              mbar_expect_tx(fullb + 8 * s, STAGE_BYTES);
              tma_ld3_mc(sb + s * STAGE_BYTES + A_BYTES + rank * 16384, bm, s * 64, bc, fullb + 8 * s);
            }
          }
          TSP(1);
          warp_poll(lane == 0 ? &fl->ln[m * 32] : nullptr, 8);
          TSP(2);
          if (lane == 0) {
#pragma unroll
            for (int s = 0; s < 4; s++) tma_ld2(sb + s * STAGE_BYTES, &maps.xn, s * 64, arow, fullb + 8 * s);
          }
          ks = 4;
          ph ^= 1;
        }
#pragma unroll 1
        for (; ks < 16; ks++) {
          const int s = ks & 3;
          mbar_wait(emptyb + 8 * s, ph);
          if (lane == 0) {
            mbar_expect_tx(fullb + 8 * s, STAGE_BYTES);
            tma_ld3_mc(sb + s * STAGE_BYTES + A_BYTES + rank * 16384, bm, ks * 64, bc, fullb + 8 * s);
            tma_ld2(sb + s * STAGE_BYTES, &maps.xn, ks * 64, arow, fullb + 8 * s);
          }
          if (s == 3) ph ^= 1;
        }
      }
      const int kh = j >> 2, bc = ((j & 3) * 256 + rank * 128) >> 6;
#pragma unroll 1
      for (int ks = 0; ks < 36; ks++) {
        if (ks == 0 || ks == 28) {
          const unsigned* p = nullptr;
          unsigned want = 2;
          const int i = (ks >> 1) + lane;
          if (lane < (ks == 0 ? 14 : 4)) {
            p = &fl->tile[m * 64 + 12 + g2_ktile(kh, i)];
          } else if (lane == 14 && ks == 0) {
            p = &fl->init[m * 32];
            want = 8;
          }
          warp_poll(p, want);
        }
        const int s = ks & 3;
        const int k0 = g2_ktile(kh, ks >> 1) * 128 + (ks & 1) * 64;
        mbar_wait(emptyb + 8 * s, ph);
        if (lane == 0) {
          mbar_expect_tx(fullb + 8 * s, STAGE_BYTES);
          tma_ld3_mc(sb + s * STAGE_BYTES + A_BYTES + rank * 16384, k0 < FF ? &maps.wd : &maps.wo,
                     k0 < FF ? k0 : k0 - FF, bc, fullb + 8 * s);
          tma_ld2(sb + s * STAGE_BYTES, &maps.hc_ld, k0, arow, fullb + 8 * s);
        }
        if (s == 3) ph ^= 1;
      }
    } else if (warp < 3) {
      const int w = warp - 1;
      const uint32_t stg = sb + STG_OFF + w * 16384;
      const int row0 = m * 128 + w * 64;
      const int nr = j < 4 ? 7 : 6;
#pragma unroll 1
      for (int r = 0; r < nr; r++) {
        const int q = (j < 4 && r >= 2) ? r - 1 : r;
        const bool kv = q == 0 || (q == 1 && j < 4);
        int col, n;
        if (q == 0) {
          col = j * 128, n = j;
        } else if (kv) {
          col = 1024 + j * 256 + (r - 1) * 128, n = r == 2 ? 8 + j : -1;
        } else if (q == ATT_SEG) {
          col = FF + j * 128, n = 40 + j;
        } else {
          n = 8 * (q < ATT_SEG ? q : q - 1) + j, col = (n - 12) * 128;
        }
        named_bar(BAR_READY + w, 160);
        if (lane == 0) {
          const CUtensorMap* mp = kv ? &maps.kv_st : &maps.hc_st;
          tma_st2(mp, col, row0, stg);
          tma_st2(mp, col + 64, row0, stg + 8192);
          bulk_commit();
          bulk_wait_read();
        }
        __syncwarp();
        if (r + 1 < nr) named_arrive(BAR_FREE + w, 160);
        if (lane == 0 && n >= 0) {
          bulk_wait_all();
          fence_async_all();
          flag_add(&fl->tile[m * 64 + n]);
        }
        __syncwarp();
      }
      named_bar(BAR_READY + w, 160);
      if (lane == 0) {
        fence_async_all();
#pragma unroll
        for (int p = 0; p < 4; p++) tma_red2(&maps.out, (j & 3) * 256 + p * 64, row0, sb + w * 8192 + p * STAGE_BYTES);
        bulk_commit();
        if (atomicAdd(&fl->done[0], 1u) == 2 * NCTA - 1) {
          for (int i = 0; i < 16; i++) {
            fl->ln[i * 32] = 0;
            fl->init[i * 32] = 0;
          }
          for (int i = 0; i < 16 * 64 / 4; i++) reinterpret_cast<uint4*>(fl->tile)[i] = make_uint4(0, 0, 0, 0);
          fl->done[0] = 0;
        }
        bulk_wait_read();
      }
    }
    __syncwarp();
    cluster_arrive();
    cluster_wait();
  } else {
    asm volatile("setmaxnreg.inc.sync.aligned.u32 232;");
    const int w = (warp >> 2) - 1, wi = warp & 3, ct = tid - 128;
    TS(0);
    {
      const int r0 = m * 128 + j * 16 + (warp - 4) * 2;
      uint4 v[2][4];
#pragma unroll
      for (int r = 0; r < 2; r++)
#pragma unroll
        for (int i = 0; i < 4; i++)
          v[r][i] = __ldg(reinterpret_cast<const uint4*>(x + (size_t)(r0 + r) * DM) + i * 32 + lane);
      float mean[2], den[2];
#pragma unroll
      for (int r = 0; r < 2; r++) {
        float s = 0.f;
#pragma unroll
        for (int i = 0; i < 4; i++) {
          const uint32_t q[4] = {v[r][i].x, v[r][i].y, v[r][i].z, v[r][i].w};
#pragma unroll
          for (int c = 0; c < 4; c++) s += bf_lo(q[c]) + bf_hi(q[c]);
        }
        mean[r] = s;
      }
#pragma unroll
      for (int o = 16; o > 0; o >>= 1) {
        mean[0] += __shfl_xor_sync(0xffffffffu, mean[0], o);
        mean[1] += __shfl_xor_sync(0xffffffffu, mean[1], o);
      }
      TS(13);
#pragma unroll
      for (int r = 0; r < 2; r++) {
        mean[r] *= (1.0f / DM);
        float s = 0.f;
#pragma unroll
        for (int i = 0; i < 4; i++) {
          const uint32_t q[4] = {v[r][i].x, v[r][i].y, v[r][i].z, v[r][i].w};
#pragma unroll
          for (int c = 0; c < 4; c++) {
            float a = bf_lo(q[c]) - mean[r], b = bf_hi(q[c]) - mean[r];
            s += a * a + b * b;
          }
        }
        den[r] = s;
      }
#pragma unroll
      for (int o = 16; o > 0; o >>= 1) {
        den[0] += __shfl_xor_sync(0xffffffffu, den[0], o);
        den[1] += __shfl_xor_sync(0xffffffffu, den[1], o);
      }
#pragma unroll
      for (int r = 0; r < 2; r++) {
        const float mb = bf_round(mean[r]);
        const float inv = 1.0f / bf_round(sqrtf(bf_round(bf_round(den[r] * (1.0f / DM)) + 1e-5f)));
#pragma unroll
        for (int i = 0; i < 4; i++) {
          const uint32_t q[4] = {v[r][i].x, v[r][i].y, v[r][i].z, v[r][i].w};
          uint32_t o[4];
#pragma unroll
          for (int c = 0; c < 4; c++) {
            const uint32_t d = pack2(bf_lo(q[c]) - mb, bf_hi(q[c]) - mb);
            o[c] = pack2(bf_lo(d) * inv, bf_hi(d) * inv);
          }
          reinterpret_cast<uint4*>(g_xn + (size_t)(r0 + r) * DM)[i * 32 + lane] = make_uint4(o[0], o[1], o[2], o[3]);
        }
      }
      TS(14);
      fence_async_all();
      named_bar(BAR_LN, 256);
      if (ct == 0) flag_add(&fl->ln[m * 32]);
      TS(15);
#pragma unroll
      for (int r = 0; r < 2; r++)
#pragma unroll
        for (int i = 0; i < 4; i++) reinterpret_cast<uint4*>(out + (size_t)(r0 + r) * DM)[i * 32 + lane] = v[r][i];
      fence_async_all();
      named_bar(BAR_LN, 256);
      if (ct == 0) flag_add(&fl->init[m * 32]);
    }
    cluster_wait();
    TS(1);

    float acc[128];
    uint32_t pk[64];
#pragma unroll
    for (int i = 0; i < 64; i++) pk[i] = 0;
    Epi e;
    const uint32_t lane_off =
        (16 * wi + (lane & 7) + ((lane >> 3) & 1) * 8) * 128 + (((lane >> 4) ^ (lane & 7)) << 4);
    e.sta = sb + STG_OFF + w * 16384 + lane_off;
    e.qptr = g_q + blockIdx.x * 2048 + ct;
    e.w = w;
    const uint32_t e0 = mapa(emptyb, 0), e1 = mapa(emptyb, 1);
    const uint32_t da = make_desc(sb + w * 8192, 16);
    const uint32_t db = make_desc(sb + A_BYTES, 8192);
    uint32_t ph = 0;
    int type = P_NONE;

#pragma unroll 1
    for (int seg = 0; seg < 5; seg++) {
      if (seg == ATT_SEG) {
        uint4 qa = e.qptr[0], qb = e.qptr[256];
        epi_drain<0>(P_GU, pk, e);
        TS(10);
        const int g = lane >> 2, t = lane & 3;
        const int dd = 16 * wi + g - 2 * t;
        const int nb = 4 - (2 * m + w);
        constexpr float SC = 0.17677669529663687f * 1.4426950408889634f;
#pragma unroll 1
        for (int h = 0; h < 4; h++) {
          const uint32_t kbase = sb + (h >> 1) * 2 * STAGE_BYTES + w * 8192 + (h & 1) * 64;
          const uint32_t dk = make_desc(kbase, 16);
          const uint32_t dv = make_desc(kbase + STAGE_BYTES, 8192);
          float s4[32];
          if ((h & 1) == 0) mbar_wait(fullb + 8 * h, ph);
          wg_fence();
          wgmma_rs_n64_z(s4, qa.x, qa.y, qa.z, qa.w, dk + 2048);
          wgmma_rs_n256_z(acc, qa.x, qa.y, qa.z, qa.w, dk);
          wgmma_rs_n64(s4, qb.x, qb.y, qb.z, qb.w, dk + 2048 + 2, 1);
          wgmma_rs_n256(acc, qb.x, qb.y, qb.z, qb.w, dk + 2, 1);
          wg_commit();
          wg_wait<0>();
          pin(acc);
          pin(s4);
          if (h & 1) release_stage(e0, e1, h - 1, lane);
          if (h < 3) {
            qa = e.qptr[(2 * h + 2) * 256];
            qb = e.qptr[(2 * h + 3) * 256];
          }
          if (nb > 0) {
#pragma unroll
            for (int i = 0; i < 128; i++)
              if ((i >> 5) < nb) acc[i] = -INFINITY;
          }
#pragma unroll
          for (int i = 0; i < 32; i++) {
            const int k0 = 8 * ((i >> 2) - ((i >> 1) & 1)) + (i & 1);
            acc[i] = (k0 > dd) ? acc[i] : s4[i];
          }
          float mx[8];
#pragma unroll
          for (int i = 0; i < 8; i++) mx[i] = acc[i];
#pragma unroll
          for (int i = 8; i < 128; i++) mx[i & 7] = fmaxf(mx[i & 7], acc[i]);
          float m0 = fmaxf(fmaxf(mx[0], mx[1]), fmaxf(mx[4], mx[5]));
          float m1 = fmaxf(fmaxf(mx[2], mx[3]), fmaxf(mx[6], mx[7]));
          m0 = fmaxf(m0, __shfl_xor_sync(0xffffffffu, m0, 1));
          m1 = fmaxf(m1, __shfl_xor_sync(0xffffffffu, m1, 1));
          m0 = fmaxf(m0, __shfl_xor_sync(0xffffffffu, m0, 2));
          m1 = fmaxf(m1, __shfl_xor_sync(0xffffffffu, m1, 2));
          const float n0 = -m0 * SC, n1 = -m1 * SC;
          float l[4] = {0.f, 0.f, 0.f, 0.f};
          float o[16];
          if ((h & 1) == 0) mbar_wait(fullb + 8 * (h + 1), ph);
#pragma unroll
          for (int cc = 0; cc < 4; cc++) {
            constexpr int ORD[4] = {1, 2, 3, 0};
            const int c = ORD[cc];
#pragma unroll
            for (int i = 0; i < 32; i++) {
              acc[32 * c + i] = ex2(fmaf(acc[32 * c + i], SC, (i & 2) ? n1 : n0));
              l[i & 3] += acc[32 * c + i];
            }
            if (cc > 0) wg_wait<0>();
            uint32_t p[16];
#pragma unroll
            for (int i = 0; i < 16; i++) p[i] = pack2(acc[32 * c + 2 * i], acc[32 * c + 2 * i + 1]);
            if (c != 0) {
              wg_fence();
#pragma unroll
              for (int q = 0; q < 4; q++) {
                if (cc == 0 && q == 0)
                  wgmma_rs_n32_tb_z(o, p[0], p[1], p[2], p[3], dv + (4 * c) * 128);
                else
                  wgmma_rs_n32_tb(o, p[4 * q], p[4 * q + 1], p[4 * q + 2], p[4 * q + 3], dv + (4 * c + q) * 128, 1);
              }
              wg_commit();
            } else {
              uint32_t p4[16];
#pragma unroll
              for (int i = 0; i < 16; i++) {
                const int k0 = 8 * ((i >> 1) - (i & 1));
                const uint32_t mk = k0 > dd ? 0xffffffffu : (k0 == dd ? 0xffff0000u : 0u);
                p4[i] = p[i] & ~mk;
                p[i] &= mk;
              }
              wg_fence();
#pragma unroll
              for (int q = 0; q < 4; q++)
                wgmma_rs_n32_tb(o, p[4 * q], p[4 * q + 1], p[4 * q + 2], p[4 * q + 3], dv + q * 128, 1);
#pragma unroll
              for (int q = 0; q < 4; q++)
                wgmma_rs_n32_tb(o, p4[4 * q], p4[4 * q + 1], p4[4 * q + 2], p4[4 * q + 3], dv + (16 + q) * 128, 1);
              wg_commit();
            }
          }
          float l0 = l[0] + l[1], l1 = l[2] + l[3];
          l0 += __shfl_xor_sync(0xffffffffu, l0, 1);
          l1 += __shfl_xor_sync(0xffffffffu, l1, 1);
          l0 += __shfl_xor_sync(0xffffffffu, l0, 2);
          l1 += __shfl_xor_sync(0xffffffffu, l1, 2);
          const float i0 = rcp(l0), i1 = rcp(l1);
          if (h == 0) named_bar(BAR_FREE + w, 160);
          wg_wait<0>();
          pin(o);
          if (h & 1) release_stage(e0, e1, h, lane);
#pragma unroll
          for (int i = 0; i < 2; i++)
            stsm4((e.sta ^ ((2 * (h & 1) + i) << 5)) + (h >> 1) * 8192, pack2(o[8 * i] * i0, o[8 * i + 1] * i0),
                  pack2(o[8 * i + 2] * i1, o[8 * i + 3] * i1), pack2(o[8 * i + 4] * i0, o[8 * i + 5] * i0),
                  pack2(o[8 * i + 6] * i1, o[8 * i + 7] * i1));
        }
        ph ^= 1;
        stage_full(e);
        type = P_NONE;
#pragma unroll
        for (int i = 0; i < 64; i++) pk[i] = 0;
        TS(11);
      }
      steps<0, 16, true>(acc, pk, e, type, fullb, e0, e1, ph, da, db, lane);
      wg_wait<0>();
      pin(acc);
      release_stage(e0, e1, 3, lane);
#pragma unroll
      for (int i = 0; i < 64; i++) pk[i] = pack2(acc[2 * i], acc[2 * i + 1]);
      const int n = 8 * seg + j;
      type = seg == 0 ? P_QK : (n < 12 ? P_V : P_GU);
      TS(2 + seg);
    }
    steps<0, 8, true>(acc, pk, e, P_GU, fullb, e0, e1, ph, da, db, lane);
    TS(7);
#pragma unroll 1
    for (int it = 0; it < 7; it++) steps<0, 4, false>(acc, pk, e, P_NONE, fullb, e0, e1, ph, da, db, lane);
    TS(8);
    wg_wait<0>();
    pin(acc);
    TS(9);
#pragma unroll
    for (int i = 0; i < 16; i++)
      stsm4(((sb + w * 8192 + lane_off) ^ ((i & 3) << 5)) + (i >> 2) * STAGE_BYTES, pack2(acc[8 * i], acc[8 * i + 1]),
            pack2(acc[8 * i + 2], acc[8 * i + 3]), pack2(acc[8 * i + 4], acc[8 * i + 5]),
            pack2(acc[8 * i + 6], acc[8 * i + 7]));
    stage_full(e);
    TS(12);
    __syncwarp();
    cluster_arrive();
    cluster_wait();
  }
}

typedef CUresult (*EncodeFn)(CUtensorMap*, CUtensorMapDataType, cuuint32_t, void*, const cuuint64_t*, const cuuint64_t*,
                             const cuuint32_t*, const cuuint32_t*, CUtensorMapInterleave, CUtensorMapSwizzle,
                             CUtensorMapL2promotion, CUtensorMapFloatOOBfill);

static void map2d(EncodeFn enc, CUtensorMap* mp, const void* p, int cols, int rows, int box_rows) {
  cuuint64_t dims[2] = {(cuuint64_t)cols, (cuuint64_t)rows};
  cuuint64_t strides[1] = {(cuuint64_t)cols * 2};
  cuuint32_t box[2] = {64, (cuuint32_t)box_rows};
  cuuint32_t es[2] = {1, 1};
  enc(mp, CU_TENSOR_MAP_DATA_TYPE_BFLOAT16, 2, const_cast<void*>(p), dims, strides, box, es,
      CU_TENSOR_MAP_INTERLEAVE_NONE, CU_TENSOR_MAP_SWIZZLE_128B, CU_TENSOR_MAP_L2_PROMOTION_L2_128B,
      CU_TENSOR_MAP_FLOAT_OOB_FILL_NONE);
}
static void map3d(EncodeFn enc, CUtensorMap* mp, const void* p, int cols, int rows) {
  cuuint64_t dims[3] = {64, (cuuint64_t)rows, (cuuint64_t)(cols / 64)};
  cuuint64_t strides[2] = {(cuuint64_t)cols * 2, 128};
  cuuint32_t box[3] = {64, 64, 2};
  cuuint32_t es[3] = {1, 1, 1};
  CUresult r = enc(mp, CU_TENSOR_MAP_DATA_TYPE_BFLOAT16, 3, const_cast<void*>(p), dims, strides, box, es,
      CU_TENSOR_MAP_INTERLEAVE_NONE, CU_TENSOR_MAP_SWIZZLE_128B, CU_TENSOR_MAP_L2_PROMOTION_L2_256B,
      CU_TENSOR_MAP_FLOAT_OOB_FILL_NONE);
  if (r != CUDA_SUCCESS) fprintf(stderr, "tensor map encode failed: %d\n", (int)r);
}

}

extern "C" void kernel_launch(void* const* d_in, const int* in_sizes, int n_in, void* d_out, int out_size) {
  using namespace fk;
  (void)in_sizes; (void)n_in; (void)out_size;
  static EncodeFn enc = nullptr;
  static void *xn, *kv, *hc;
  if (!enc) {
    void* fn = nullptr;
    cudaDriverEntryPointQueryResult qr;
    cudaGetDriverEntryPoint("cuTensorMapEncodeTiled", &fn, cudaEnableDefault, &qr);
    enc = (EncodeFn)fn;
    cudaGetSymbolAddress(&xn, g_xn);
    cudaGetSymbolAddress(&kv, g_kv);
    cudaGetSymbolAddress(&hc, g_hc);
    cudaFuncSetAttribute(fused_kernel, cudaFuncAttributeMaxDynamicSharedMemorySize, SMEM_BYTES);
  }
  Maps maps;
  map2d(enc, &maps.xn, xn, DM, SEQ, 128);
  map3d(enc, &maps.wqkv, d_in[1], 3 * DM, DM);
  map3d(enc, &maps.wo, d_in[2], DM, DM);
  map3d(enc, &maps.wg, d_in[4], FF, DM);
  map3d(enc, &maps.wu, d_in[5], FF, DM);
  map3d(enc, &maps.wd, d_in[6], DM, FF);
  map2d(enc, &maps.kv_st, kv, 2 * DM, SEQ, 64);
  map2d(enc, &maps.kv_ld, kv, 2 * DM, SEQ, 128);
  map2d(enc, &maps.hc_st, hc, KC, SEQ, 64);
  map2d(enc, &maps.hc_ld, hc, KC, SEQ, 128);
  map2d(enc, &maps.out, d_out, DM, SEQ, 64);
  fused_kernel<<<NCTA, NTHREADS, SMEM_BYTES>>>(maps, (const __nv_bfloat16*)d_in[0], (__nv_bfloat16*)d_out);
}
```

```cpp
#include <cuda_runtime.h>
#include <cuda_bf16.h>
#include <cuda.h>
#include <stdint.h>

namespace fk {

constexpr int SEQ = 2048, DM = 1024, FF = 3584, KC = FF + DM;
constexpr int STAGES = 4;
constexpr int A_BYTES = 128 * 64 * 2, B_BYTES = 256 * 64 * 2, STAGE_BYTES = A_BYTES + B_BYTES;
constexpr int STG_OFF = STAGES * STAGE_BYTES;
constexpr int KV_OFF = STG_OFF + 16384;
constexpr int BAR_OFF = KV_OFF + 16384;
constexpr int ONES_OFF = BAR_OFF + 1024;
constexpr int SMEM_BYTES = ONES_OFF + 1024;
constexpr int NCTA = 128, NTHREADS = 384;
constexpr unsigned SPIN_LIMIT = 1u << 15;

struct Flags {
  unsigned ln[16 * 32];
  unsigned cs[8 * 32];
  unsigned tile[16 * 64];
  unsigned done[32];
};

struct Maps {
  CUtensorMap xr, cs, xn, wqkv, wg, wu, wd, wo, kv_st, kv_ld, hc_st, hc_ld, o_st, out;
};

__device__ __align__(1024) __nv_bfloat16 g_xn[SEQ * DM];
__device__ __align__(1024) __nv_bfloat16 g_kv[SEQ * 2 * DM];
__device__ __align__(1024) __nv_bfloat16 g_hc[SEQ * KC];
__device__ __align__(1024) uint4 g_q[NCTA * 8 * 256];
__device__ __align__(1024) uint32_t g_cs[16 * DM];
__device__ __align__(1024) uint2 g_st[SEQ];
__device__ __align__(1024) Flags g_flags;

#define ACC8(d, i) "+f"(d[i]), "+f"(d[i + 1]), "+f"(d[i + 2]), "+f"(d[i + 3]), "+f"(d[i + 4]), "+f"(d[i + 5]), "+f"(d[i + 6]), "+f"(d[i + 7])
#define OUT8(d, i) "=f"(d[i]), "=f"(d[i + 1]), "=f"(d[i + 2]), "=f"(d[i + 3]), "=f"(d[i + 4]), "=f"(d[i + 5]), "=f"(d[i + 6]), "=f"(d[i + 7])
#define ACC4(d, i) "+f"(d[i]), "+f"(d[i + 1]), "+f"(d[i + 2]), "+f"(d[i + 3])
#define OUT4(d, i) "=f"(d[i]), "=f"(d[i + 1]), "=f"(d[i + 2]), "=f"(d[i + 3])
__device__ __forceinline__ void wgmma_rs_n64_z(float (&d)[32], uint32_t a0, uint32_t a1, uint32_t a2, uint32_t a3,
    uint32_t db) {
  asm volatile("{\n.reg .b64 db;\n"
    "mov.b64 db, {%36, 0x80000020};\n"
    "wgmma.mma_async.sync.aligned.m64n64k16.f32.bf16.bf16 {"
    "%0, %1, %2, %3, %4, %5, %6, %7, %8, %9, %10, %11, %12, %13, %14, %15, %16, %17, %18, %19, %20, %21, %22, %23, "
    "%24, %25, %26, %27, %28, %29, %30, %31"
    "}, {%32, %33, %34, %35}, db, 0, 1, 1, 0;\n}\n"
    : OUT8(d, 0), OUT8(d, 8), OUT8(d, 16), OUT8(d, 24)
    : "r"(a0), "r"(a1), "r"(a2), "r"(a3), "r"(db));
}

__device__ __forceinline__ void wgmma_rs_n40_tb_z(float (&d)[20], uint32_t a0, uint32_t a1, uint32_t a2, uint32_t a3,
    uint32_t db) {
  asm volatile("{\n.reg .b64 db;\n"
    "mov.b64 db, {%24, 0x80000020};\n"
    "wgmma.mma_async.sync.aligned.m64n40k16.f32.bf16.bf16 {"
    "%0, %1, %2, %3, %4, %5, %6, %7, %8, %9, %10, %11, %12, %13, %14, %15, %16, %17, %18, %19"
    "}, {%20, %21, %22, %23}, db, 0, 1, 1, 1;\n}\n"
    : OUT8(d, 0), OUT8(d, 8), OUT4(d, 16)
    : "r"(a0), "r"(a1), "r"(a2), "r"(a3), "r"(db));
}

__device__ __forceinline__ void wgmma_ss_n256_tb(float (&d)[128], uint32_t da, uint32_t db, int sd) {
  asm volatile("{\n.reg .pred p;\n.reg .b64 da, db;\nsetp.ne.b32 p, %130, 0;\n"
    "mov.b64 da, {%128, 0x40000040};\nmov.b64 db, {%129, 0x40000040};\n"
    "wgmma.mma_async.sync.aligned.m64n256k16.f32.bf16.bf16 {"
    "%0, %1, %2, %3, %4, %5, %6, %7, %8, %9, %10, %11, %12, %13, %14, %15, %16, %17, %18, %19, %20, %21, %22, %23, "
    "%24, %25, %26, %27, %28, %29, %30, %31, %32, %33, %34, %35, %36, %37, %38, %39, %40, %41, %42, %43, %44, %45, "
    "%46, %47, %48, %49, %50, %51, %52, %53, %54, %55, %56, %57, %58, %59, %60, %61, %62, %63, %64, %65, %66, %67, "
    "%68, %69, %70, %71, %72, %73, %74, %75, %76, %77, %78, %79, %80, %81, %82, %83, %84, %85, %86, %87, %88, %89, "
    "%90, %91, %92, %93, %94, %95, %96, %97, %98, %99, %100, %101, %102, %103, %104, %105, %106, %107, %108, %109, "
    "%110, %111, %112, %113, %114, %115, %116, %117, %118, %119, %120, %121, %122, %123, %124, %125, %126, %127"
    "}, da, db, p, 1, 1, 0, 1;\n}\n"
    : ACC8(d, 0), ACC8(d, 8), ACC8(d, 16), ACC8(d, 24), ACC8(d, 32), ACC8(d, 40), ACC8(d, 48), ACC8(d, 56), ACC8(d, 64), ACC8(d, 72), ACC8(d, 80), ACC8(d, 88), ACC8(d, 96), ACC8(d, 104), ACC8(d, 112), ACC8(d, 120)
    : "r"(da), "r"(db), "r"(sd));
}

__device__ __forceinline__ void wgmma_rs_n64(float (&d)[32], uint32_t a0, uint32_t a1, uint32_t a2, uint32_t a3,
    uint32_t db, int sd) {
  asm volatile("{\n.reg .pred p;\n.reg .b64 db;\nsetp.ne.b32 p, %37, 0;\n"
    "mov.b64 db, {%36, 0x80000020};\n"
    "wgmma.mma_async.sync.aligned.m64n64k16.f32.bf16.bf16 {"
    "%0, %1, %2, %3, %4, %5, %6, %7, %8, %9, %10, %11, %12, %13, %14, %15, %16, %17, %18, %19, %20, %21, %22, %23, "
    "%24, %25, %26, %27, %28, %29, %30, %31"
    "}, {%32, %33, %34, %35}, db, p, 1, 1, 0;\n}\n"
    : ACC8(d, 0), ACC8(d, 8), ACC8(d, 16), ACC8(d, 24)
    : "r"(a0), "r"(a1), "r"(a2), "r"(a3), "r"(db), "r"(sd));
}

__device__ __forceinline__ void wgmma_rs_n40_tb(float (&d)[20], uint32_t a0, uint32_t a1, uint32_t a2, uint32_t a3,
    uint32_t db, int sd) {
  asm volatile("{\n.reg .pred p;\n.reg .b64 db;\nsetp.ne.b32 p, %25, 0;\n"
    "mov.b64 db, {%24, 0x80000020};\n"
    "wgmma.mma_async.sync.aligned.m64n40k16.f32.bf16.bf16 {"
    "%0, %1, %2, %3, %4, %5, %6, %7, %8, %9, %10, %11, %12, %13, %14, %15, %16, %17, %18, %19"
    "}, {%20, %21, %22, %23}, db, p, 1, 1, 1;\n}\n"
    : ACC8(d, 0), ACC8(d, 8), ACC4(d, 16)
    : "r"(a0), "r"(a1), "r"(a2), "r"(a3), "r"(db), "r"(sd));
}

__device__ __forceinline__ void wgmma_rs_n256_tb(float (&d)[128], uint32_t a0, uint32_t a1, uint32_t a2, uint32_t a3,
    uint32_t db, int sd) {
  asm volatile("{\n.reg .pred p;\n.reg .b64 db;\nsetp.ne.b32 p, %133, 0;\n"
    "mov.b64 db, {%132, 0x40000040};\n"
    "wgmma.mma_async.sync.aligned.m64n256k16.f32.bf16.bf16 {"
    "%0, %1, %2, %3, %4, %5, %6, %7, %8, %9, %10, %11, %12, %13, %14, %15, %16, %17, %18, %19, %20, %21, %22, %23, "
    "%24, %25, %26, %27, %28, %29, %30, %31, %32, %33, %34, %35, %36, %37, %38, %39, %40, %41, %42, %43, %44, %45, "
    "%46, %47, %48, %49, %50, %51, %52, %53, %54, %55, %56, %57, %58, %59, %60, %61, %62, %63, %64, %65, %66, %67, "
    "%68, %69, %70, %71, %72, %73, %74, %75, %76, %77, %78, %79, %80, %81, %82, %83, %84, %85, %86, %87, %88, %89, "
    "%90, %91, %92, %93, %94, %95, %96, %97, %98, %99, %100, %101, %102, %103, %104, %105, %106, %107, %108, %109, "
    "%110, %111, %112, %113, %114, %115, %116, %117, %118, %119, %120, %121, %122, %123, %124, %125, %126, %127"
    "}, {%128, %129, %130, %131}, db, p, 1, 1, 1;\n}\n"
    : ACC8(d, 0), ACC8(d, 8), ACC8(d, 16), ACC8(d, 24), ACC8(d, 32), ACC8(d, 40), ACC8(d, 48), ACC8(d, 56), ACC8(d, 64), ACC8(d, 72), ACC8(d, 80), ACC8(d, 88), ACC8(d, 96), ACC8(d, 104), ACC8(d, 112), ACC8(d, 120)
    : "r"(a0), "r"(a1), "r"(a2), "r"(a3), "r"(db), "r"(sd));
}


__device__ __forceinline__ void wg_fence() { asm volatile("wgmma.fence.sync.aligned;" ::: "memory"); }
__device__ __forceinline__ void wg_commit() { asm volatile("wgmma.commit_group.sync.aligned;" ::: "memory"); }
template <int N>
__device__ __forceinline__ void wg_wait() { asm volatile("wgmma.wait_group.sync.aligned %0;" ::"n"(N) : "memory"); }
template <int N>
__device__ __forceinline__ void pin(float (&d)[N]) {
#pragma unroll
  for (int i = 0; i < N; i++) asm volatile("" : "+f"(d[i])::"memory");
}
__device__ __forceinline__ void mbar_init(uint32_t bar, uint32_t cnt) {
  asm volatile("mbarrier.init.shared::cta.b64 [%0], %1;" ::"r"(bar), "r"(cnt) : "memory");
}
template <unsigned LIMIT = SPIN_LIMIT>
__device__ __forceinline__ void mbar_wait(uint32_t bar, uint32_t parity) {
  asm volatile(
      "{\n.reg .pred p;\n.reg .u32 n;\nmov.u32 n, 0;\n"
      "WAIT_LOOP:\nmbarrier.try_wait.parity.shared::cta.b64 p, [%0], %1;\n@p bra WAIT_DONE;\n"
      "add.u32 n, n, 1;\nsetp.lt.u32 p, n, %2;\n@p bra WAIT_LOOP;\nWAIT_DONE:\n}\n" ::"r"(bar),
      "r"(parity), "n"(LIMIT)
      : "memory");
}
__device__ __forceinline__ bool mbar_test(uint32_t bar, uint32_t parity) {
  uint32_t ok;
  asm volatile("{\n.reg .pred p;\nmbarrier.test_wait.parity.shared::cta.b64 p, [%1], %2;\nselp.u32 %0, 1, 0, p;\n}\n"
               : "=r"(ok)
               : "r"(bar), "r"(parity)
               : "memory");
  return ok != 0;
}
__device__ __forceinline__ uint4 ld_q(const uint4* p) {
  uint4 v;
  asm volatile("ld.global.v4.u32 {%0, %1, %2, %3}, [%4];" : "=r"(v.x), "=r"(v.y), "=r"(v.z), "=r"(v.w) : "l"(p) : "memory");
  return v;
}
__device__ __forceinline__ int lane_id() {
  int l;
  asm volatile("mov.u32 %0, %%laneid;" : "=r"(l));
  return l;
}
__device__ __forceinline__ bool elect() {
  uint32_t p;
  asm volatile("{\n.reg .pred P;\nelect.sync _|P, 0xffffffff;\nselp.u32 %0, 1, 0, P;\n}\n" : "=r"(p));
  return p != 0;
}
__device__ __forceinline__ void mbar_expect_tx(uint32_t bar, uint32_t bytes) {
  asm volatile("mbarrier.arrive.expect_tx.shared::cta.b64 _, [%0], %1;" ::"r"(bar), "r"(bytes) : "memory");
}
__device__ __forceinline__ void mbar_arrive_cluster(uint32_t addr) {
  asm volatile("mbarrier.arrive.shared::cluster.b64 _, [%0];" ::"r"(addr) : "memory");
}
__device__ __forceinline__ void mbar_arrive(uint32_t bar) {
  asm volatile("mbarrier.arrive.shared::cta.b64 _, [%0];" ::"r"(bar) : "memory");
}
__device__ __forceinline__ uint32_t mapa(uint32_t addr, uint32_t rank) {
  uint32_t r;
  asm("mapa.shared::cluster.u32 %0, %1, %2;" : "=r"(r) : "r"(addr), "r"(rank));
  return r;
}
__device__ __forceinline__ uint64_t pol_first() {
  uint64_t p;
  asm("createpolicy.fractional.L2::evict_first.b64 %0, 1.0;" : "=l"(p));
  return p;
}
__device__ __forceinline__ void tma_ld2(uint32_t dst, const CUtensorMap* m, int c0, int c1, uint32_t bar) {
  asm volatile(
      "cp.async.bulk.tensor.2d.shared::cluster.global.mbarrier::complete_tx::bytes [%0], [%1, {%3, %4}], [%2];" ::"r"(dst),
      "l"(m), "r"(bar), "r"(c0), "r"(c1)
      : "memory");
}
__device__ __forceinline__ void tma_ld2_last(uint32_t dst, const CUtensorMap* m, int c0, int c1, uint32_t bar) {
  asm volatile(
      "cp.async.bulk.tensor.2d.shared::cluster.global.mbarrier::complete_tx::bytes.L2::cache_hint "
      "[%0], [%1, {%3, %4}], [%2], %5;" ::"r"(dst),
      "l"(m), "r"(bar), "r"(c0), "r"(c1), "l"(pol_first())
      : "memory");
}
__device__ __forceinline__ void tma_ld3_mc(uint32_t dst, const CUtensorMap* m, int c1, int c2, uint32_t bar) {
  asm volatile(
      "cp.async.bulk.tensor.3d.shared::cluster.global.mbarrier::complete_tx::bytes.multicast::cluster.L2::cache_hint "
      "[%0], [%1, {%3, %4, %5}], [%2], %6, %7;" ::"r"(dst),
      "l"(m), "r"(bar), "r"(0), "r"(c1), "r"(c2), "h"((uint16_t)3), "l"(pol_first())
      : "memory");
}
__device__ __forceinline__ void bulk_ld(uint32_t dst, const void* src, uint32_t bytes, uint32_t bar) {
  asm volatile("cp.async.bulk.shared::cluster.global.mbarrier::complete_tx::bytes [%0], [%1], %2, [%3];" ::"r"(dst), "l"(src),
               "r"(bytes), "r"(bar)
               : "memory");
}
__device__ __forceinline__ void bulk_st(void* dst, uint32_t src, uint32_t bytes) {
  asm volatile("cp.async.bulk.global.shared::cta.bulk_group [%0], [%1], %2;" ::"l"(dst), "r"(src), "r"(bytes) : "memory");
}
__device__ __forceinline__ void tma_st2(const CUtensorMap* m, int c0, int c1, uint32_t src) {
  asm volatile("cp.async.bulk.tensor.2d.global.shared::cta.bulk_group [%0, {%2, %3}], [%1];" ::"l"(m), "r"(src),
               "r"(c0), "r"(c1)
               : "memory");
}
__device__ __forceinline__ void tma_red2(const CUtensorMap* m, int c0, int c1, uint32_t src) {
  asm volatile("cp.reduce.async.bulk.tensor.2d.global.shared::cta.add.tile.bulk_group [%0, {%2, %3}], [%1];" ::"l"(m),
               "r"(src), "r"(c0), "r"(c1)
               : "memory");
}
__device__ __forceinline__ void bulk_commit() { asm volatile("cp.async.bulk.commit_group;" ::: "memory"); }
__device__ __forceinline__ void bulk_wait_all() { asm volatile("cp.async.bulk.wait_group 0;" ::: "memory"); }
__device__ __forceinline__ void bulk_wait_read() { asm volatile("cp.async.bulk.wait_group.read 0;" ::: "memory"); }
__device__ __forceinline__ void fence_async_smem() { asm volatile("fence.proxy.async.shared::cta;" ::: "memory"); }
__device__ __forceinline__ void fence_async_all() { asm volatile("fence.proxy.async.global;" ::: "memory"); }
__device__ __forceinline__ void named_bar(int id, int n) { asm volatile("bar.sync %0, %1;" ::"r"(id), "r"(n) : "memory"); }
__device__ __forceinline__ void named_arrive(int id, int n) {
  asm volatile("bar.arrive %0, %1;" ::"r"(id), "r"(n) : "memory");
}
__device__ __forceinline__ void cluster_arrive_relaxed() {
  asm volatile("barrier.cluster.arrive.relaxed.aligned;" ::: "memory");
}
__device__ __forceinline__ void cluster_wait() { asm volatile("barrier.cluster.wait.acquire.aligned;" ::: "memory"); }
__device__ __forceinline__ void flag_add(unsigned* p) {
  asm volatile("red.release.gpu.global.add.u32 [%0], 1;" ::"l"(p) : "memory");
}
__device__ __forceinline__ unsigned ld_acq(const unsigned* p) {
  unsigned v;
  asm volatile("ld.acquire.gpu.global.u32 %0, [%1];" : "=r"(v) : "l"(p) : "memory");
  return v;
}
__device__ __forceinline__ void warp_poll(const unsigned* p, unsigned want) {
  if (p) {
    unsigned n = 0;
    while (ld_acq(p) < want && ++n < 4 * SPIN_LIMIT) {
    }
  }
  __syncwarp();
  fence_async_all();
}
__device__ __forceinline__ void stsm4(uint32_t addr, uint32_t a, uint32_t b, uint32_t c, uint32_t d) {
  asm volatile("stmatrix.sync.aligned.m8n8.x4.shared.b16 [%0], {%1, %2, %3, %4};" ::"r"(addr), "r"(a), "r"(b), "r"(c),
               "r"(d)
               : "memory");
}
__device__ __forceinline__ uint32_t pack2(float lo, float hi) {
  uint32_t r;
  asm("cvt.rn.bf16x2.f32 %0, %1, %2;" : "=r"(r) : "f"(hi), "f"(lo));
  return r;
}
__device__ __forceinline__ float bf_lo(uint32_t v) { return __uint_as_float(v << 16); }
__device__ __forceinline__ float bf_hi(uint32_t v) { return __uint_as_float(v & 0xffff0000u); }
__device__ __forceinline__ float bf_round(float v) { return __bfloat162float(__float2bfloat16_rn(v)); }
__device__ __forceinline__ float ex2(float x) {
  float y;
  asm("ex2.approx.ftz.f32 %0, %1;" : "=f"(y) : "f"(x));
  return y;
}
__device__ __forceinline__ float rcp(float x) {
  float y;
  asm("rcp.approx.ftz.f32 %0, %1;" : "=f"(y) : "f"(x));
  return y;
}
__device__ __forceinline__ uint32_t make_desc(uint32_t addr, uint32_t lbo) { return ((addr & 0x3FFFF) >> 4) | ((lbo >> 4) << 16); }
__device__ __forceinline__ void release_stage(uint32_t e0, uint32_t e1, int st) {
  if (elect()) {
    mbar_arrive_cluster(e0 + 8 * st);
    mbar_arrive_cluster(e1 + 8 * st);
  }
}
__device__ __forceinline__ uint32_t glu2(uint32_t g, uint32_t u) {
  constexpr float NL2E = -1.4426950408889634f;
  float s0 = rcp(1.0f + ex2(bf_lo(g) * NL2E));
  float s1 = rcp(1.0f + ex2(bf_hi(g) * NL2E));
  return pack2(s0 * bf_lo(u), s1 * bf_hi(u));
}

enum { P_QK = 1, P_V = 2, P_GU = 3 };

__device__ __forceinline__ int g2_slice(int kh, int ks) {
  return ks < 20 ? 20 * kh + ks : (ks < 24 ? 16 + 8 * kh + 2 * ks : (ks < 32 ? 16 + 8 * kh + ks : 8 * kh + 2 * ks - 7));
}

constexpr int BAR_READY = 1, BAR_FREE = 3, BAR_SKEW = 5, BAR_WG = 6, BAR_LN = 8;

struct Epi {
  uint32_t sta;
  uint4* qptr;
  int w;
};
__device__ __forceinline__ void stage_full(const Epi& e) {
  fence_async_smem();
  named_arrive(BAR_READY + e.w, 160);
}

template <int S>
__device__ __forceinline__ void epi_chunk(int type, const uint32_t (&pk)[64], const Epi& e) {
  if (type == P_GU) {
    if (S < 8) {
      uint32_t h0 = glu2(pk[(4 * S) & 31], pk[32 + ((4 * S) & 31)]);
      uint32_t h1 = glu2(pk[(4 * S + 1) & 31], pk[32 + ((4 * S + 1) & 31)]);
      uint32_t h2 = glu2(pk[(4 * S + 2) & 31], pk[32 + ((4 * S + 2) & 31)]);
      uint32_t h3 = glu2(pk[(4 * S + 3) & 31], pk[32 + ((4 * S + 3) & 31)]);
      if ((S & 3) == 0) named_bar(BAR_FREE + e.w, 160);
      stsm4(e.sta ^ ((S & 3) << 5), h0, h1, h2, h3);
      if ((S & 3) == 3) stage_full(e);
    }
  } else if (type == P_QK) {
    if (S < 8) {
      constexpr int I = S & 7;
      if ((S & 3) == 0) named_bar(BAR_FREE + e.w, 160);
      stsm4(e.sta ^ ((I & 3) << 5), pk[32 + 4 * I], pk[33 + 4 * I], pk[34 + 4 * I], pk[35 + 4 * I]);
      if ((S & 3) == 3) stage_full(e);
      if ((S & 3) == 1)
#pragma unroll
        for (int i = I - 1; i <= I + 2; i++)
          e.qptr[i * 256] = make_uint4(pk[4 * i], pk[4 * i + 1], pk[4 * i + 2], pk[4 * i + 3]);
    }
  } else {
    if (S < 8 && (S & 1) == 0) {
      constexpr int R = (S >> 1) & 3;
      named_bar(BAR_FREE + e.w, 160);
#pragma unroll
      for (int i = 0; i < 4; i++)
        stsm4(e.sta ^ (i << 5), pk[16 * R + 4 * i], pk[16 * R + 4 * i + 1], pk[16 * R + 4 * i + 2], pk[16 * R + 4 * i + 3]);
      stage_full(e);
    }
  }
}

constexpr int LN_A0 = 3, LN_A1 = 5, LN_B0 = 4, LN_B1 = 6;
constexpr int CS_AT = 6;
constexpr int SKN = 2;
__device__ __forceinline__ void colsum(float (&d)[4], uint32_t tile, uint32_t dst, int cw, bool last) {
  const int lane = lane_id();
  const uint32_t one = (lane & 4) ? 0x3f800000u : 0x3f80u;
  const uint32_t b0 = (lane & 8) ? 0u : one, b1 = one - b0;
  const int r7 = 2 * (lane & 3) + ((lane >> 3) & 1);
  const uint32_t ad = tile + (cw >> 2) * 8192 + ((lane >> 4) * 8 + r7) * 128 + (((2 * (cw & 3) + ((lane >> 2) & 1)) ^ r7) << 4);
  uint32_t t[16];
#pragma unroll
  for (int i = 0; i < 4; i++)
    asm volatile("ld.shared.v4.u32 {%0, %1, %2, %3}, [%4];"
                 : "=r"(t[4 * i]), "=r"(t[4 * i + 1]), "=r"(t[4 * i + 2]), "=r"(t[4 * i + 3])
                 : "r"(ad + i * 2048)
                 : "memory");
#pragma unroll
  for (int i = 0; i < 4; i++)
    asm("mma.sync.aligned.m16n8k16.row.col.f32.bf16.bf16.f32 {%0, %1, %2, %3}, {%4, %5, %6, %7}, {%8, %9}, {%0, %1, %2, %3};"
        : "+f"(d[0]), "+f"(d[1]), "+f"(d[2]), "+f"(d[3])
        : "r"(t[4 * i]), "r"(t[4 * i + 1]), "r"(t[4 * i + 2]), "r"(t[4 * i + 3]), "r"(b0), "r"(b1));
  if (last) {
#pragma unroll
    for (int o = 8; o < 32; o <<= 1)
#pragma unroll
      for (int i = 0; i < 4; i++) d[i] += __shfl_xor_sync(0xffffffffu, d[i], o);
    uint32_t v0 = pack2(d[0], d[1]), v1 = pack2(d[2], d[3]);
    if (lane & 2) v0 = pack2(d[0] - bf_lo(v0), d[1] - bf_hi(v0)), v1 = pack2(d[2] - bf_lo(v1), d[3] - bf_hi(v1));
    if (lane < 8)
      asm volatile("st.shared.v2.u32 [%0], {%1, %2};" ::"r"(dst + (lane & 2) * 128 + cw * 32 + (lane & 4) * 4 + (lane & 1) * 8),
                   "r"(v0), "r"(v1)
                   : "memory");
    fence_async_smem();
    named_arrive(BAR_LN + 2, 288);
  }
}
__device__ __forceinline__ void lds4(uint32_t (&q)[4], uint32_t ad) {
  asm volatile("ld.shared.v4.u32 {%0, %1, %2, %3}, [%4];" : "=r"(q[0]), "=r"(q[1]), "=r"(q[2]), "=r"(q[3]) : "r"(ad) : "memory");
}
__device__ __forceinline__ float warp_sum(float v) {
#pragma unroll
  for (int o = 16; o > 0; o >>= 1) v += __shfl_xor_sync(0xffffffffu, v, o);
  return v;
}
__device__ __forceinline__ void ln_row(uint32_t sb, int r) {
  const int lane = lane_id();
  const uint32_t ad = sb + STG_OFF + r * 2048 + lane * 16;
  uint32_t q[4][4];
  if (r < 8) mbar_wait(sb + BAR_OFF + 152, 0);
#pragma unroll
  for (int u = 0; u < 4; u++) lds4(q[u], ad + u * 512);
  float s[4] = {0.f, 0.f, 0.f, 0.f};
#pragma unroll
  for (int c = 0; c < 16; c++) s[2 * (c & 1)] += bf_lo(q[c >> 2][c & 3]), s[2 * (c & 1) + 1] += bf_hi(q[c >> 2][c & 3]);
  const float mean = warp_sum((s[0] + s[1]) + (s[2] + s[3])) * (1.0f / DM);
  s[0] = s[1] = s[2] = s[3] = 0.f;
#pragma unroll
  for (int c = 0; c < 16; c++) {
    const float a = bf_lo(q[c >> 2][c & 3]) - mean, b = bf_hi(q[c >> 2][c & 3]) - mean;
    s[2 * (c & 1)] = fmaf(a, a, s[2 * (c & 1)]);
    s[2 * (c & 1) + 1] = fmaf(b, b, s[2 * (c & 1) + 1]);
  }
  const float var = warp_sum((s[0] + s[1]) + (s[2] + s[3])) * (1.0f / DM);
  const uint32_t mb = pack2(mean, mean);
  float sd;
  asm("sqrt.approx.f32 %0, %1;" : "=f"(sd) : "f"(bf_round(bf_round(var) + 1e-5f)));
  const float inv = rcp(bf_round(sd));
  if (r < 8) mbar_wait(sb + BAR_OFF + 160, 0);
  if (lane == 0)
    asm volatile("st.shared.v2.u32 [%0], {%1, %2};" ::"r"(sb + BAR_OFF + 256 + r * 8), "r"(mb ^ 0x80008000u), "f"(inv) : "memory");
#pragma unroll
  for (int u = 0; u < 4; u++) {
#pragma unroll
    for (int c = 0; c < 4; c++) {
      uint32_t d;
      asm("sub.rn.bf16x2 %0, %1, %2;" : "=r"(d) : "r"(q[u][c]), "r"(mb));
      q[u][c] = pack2(bf_lo(d) * inv, bf_hi(d) * inv);
    }
    asm volatile("st.shared.v4.u32 [%0], {%1, %2, %3, %4};" ::"r"(ad + u * 512), "r"(q[u][0]), "r"(q[u][1]), "r"(q[u][2]),
                 "r"(q[u][3])
                 : "memory");
  }
}

template <int S, int END, bool FRESH>
__device__ __forceinline__ void steps(float (&acc)[128], const uint32_t (&pk)[64], const Epi& e, int type, uint32_t fullb,
                                      uint32_t e0, uint32_t e1, uint32_t& ph, uint32_t da, uint32_t db) {
  constexpr int ST = S & 3;
  mbar_wait(fullb + 8 * ST, ph);
  wg_fence();
#pragma unroll
  for (int kk = 0; kk < 4; kk++)
    wgmma_ss_n256_tb(acc, da + (ST * (STAGE_BYTES >> 4) + kk * 2), db + (ST * (STAGE_BYTES >> 4) + kk * 128),
                     (FRESH && S == 0 && kk == 0) ? 0 : 1);
  wg_commit();
  if (S > 0 || !FRESH) {
    wg_wait<1>();
    release_stage(e0, e1, (S + 3) & 3);
  }
  epi_chunk<S>(type, pk, e);
  if (ST == 3) ph ^= 1;
  if constexpr (S + 1 < END) steps<S + 1, END, FRESH>(acc, pk, e, type, fullb, e0, e1, ph, da, db);
}

struct Att {
  uint4 qa, qb;
  uint32_t p[16];
  float o[20];
  float m0, m1;
};
template <int T>
__device__ __forceinline__ void att_steps(float (&acc)[128], Att& a, const Epi& e, int h, int nb, uint32_t sb,
                                          uint32_t e0, uint32_t e1, uint32_t& ph, uint32_t da, uint32_t db, int wi,
                                          bool ready) {
  constexpr int ST = T & 3;
  constexpr float SC = 0.17677669529663687f * 1.4426950408889634f;
  const uint32_t fullb = sb + BAR_OFF, kvfull = fullb + 64, kvempty = fullb + 80, priv = fullb + 96;
  float s[32];
  if (T == 0 || !ready) {
    if (T < 5) mbar_wait(kvfull + 8 * (T & 1), (T & 1) ? (T >> 1) : ((h + (T >> 1)) & 1));
    if (T == 4) mbar_wait(priv + 8 * e.w, h & 1);
    mbar_wait(fullb + 8 * ST, ph);
  }
  wg_fence();
  if (T < 6) {
    const uint32_t dsh = make_desc(sb + KV_OFF + (T & 1) * 8192, 16);
    const uint32_t dpr = make_desc(sb + STG_OFF + e.w * 8192, 16);
    if (T < 5) {
      const uint32_t dk = T < 4 ? dsh : dpr;
      wgmma_rs_n64_z(s, a.qa.x, a.qa.y, a.qa.z, a.qa.w, dk);
      wgmma_rs_n64(s, a.qb.x, a.qb.y, a.qb.z, a.qb.w, dk + 2, 1);
      if (T > 0) wg_commit();
    }
    if (T > 0) {
      const uint32_t va = (T < 5 ? KV_OFF + (T & 1) * 8192 : STG_OFF + e.w * 8192) + 4096;
      const uint32_t dv = make_desc(sb + va, ONES_OFF - va);
#pragma unroll
      for (int q = 0; q < 4; q++) {
        if (T == 1 && q == 0)
          wgmma_rs_n40_tb_z(a.o, a.p[0], a.p[1], a.p[2], a.p[3], dv);
        else
          wgmma_rs_n40_tb(a.o, a.p[4 * q], a.p[4 * q + 1], a.p[4 * q + 2], a.p[4 * q + 3], dv + q * 64 - ((q * 64) << 16), 1);
      }
    }
    wg_commit();
  }
#pragma unroll
  for (int kk = 0; kk < 4; kk++)
    wgmma_ss_n256_tb(acc, da + (ST * (STAGE_BYTES >> 4) + kk * 2), db + (ST * (STAGE_BYTES >> 4) + kk * 128), 1);
  wg_commit();
  wg_wait<(T > 0 && T < 5) ? 2 : 1>();
  release_stage(e0, e1, (T + 3) & 3);
  if (ST == 3) ph ^= 1;
  if (T < 5) {
    ready = mbar_test(fullb + 8 * ((T + 1) & 3), ph);
    if (T < 4) ready &= mbar_test(kvfull + 8 * ((T + 1) & 1), (T & 1) ? ((h + ((T + 1) >> 1)) & 1) : (T >> 1));
    if (T == 3) ready &= mbar_test(priv + 8 * e.w, h & 1);
  }
  if (T == 5) pin(a.o);
  if (T < 5) {
    pin(s);
    if (T == 4 || (T == 0 && e.w == 1) || (T == 3 && e.w == 0)) {
      const int lane = lane_id();
      const int dd = 16 * wi + (lane >> 2) - 2 * (lane & 3);
      const bool diag = T == 4 ? e.w == 1 : T == 3;
#pragma unroll
      for (int i = 0; i < 32; i++) {
        const int k0 = 8 * ((i >> 2) - ((i >> 1) & 1)) + (i & 1);
        s[i] = ((k0 > dd) != diag) ? s[i] : -INFINITY;
      }
    }
    float mx[8];
#pragma unroll
    for (int i = 0; i < 8; i++) mx[i] = s[i];
#pragma unroll
    for (int i = 8; i < 32; i++) mx[i & 7] = fmaxf(mx[i & 7], s[i]);
    float c0 = fmaxf(fmaxf(mx[0], mx[1]), fmaxf(mx[4], mx[5]));
    float c1 = fmaxf(fmaxf(mx[2], mx[3]), fmaxf(mx[6], mx[7]));
    c0 = fmaxf(c0, __shfl_xor_sync(0xffffffffu, c0, 1));
    c1 = fmaxf(c1, __shfl_xor_sync(0xffffffffu, c1, 1));
    c0 = fmaxf(c0, __shfl_xor_sync(0xffffffffu, c0, 2));
    c1 = fmaxf(c1, __shfl_xor_sync(0xffffffffu, c1, 2));
    const bool dead = (T < 4 ? T + 1 : 5 * e.w) < nb;
    if (dead) c0 = c1 = -INFINITY;
    if (T > 0) {
      c0 = fmaxf(c0, a.m0);
      c1 = fmaxf(c1, a.m1);
    }
    const float u0 = c0 == -INFINITY ? 0.f : c0 * SC, u1 = c1 == -INFINITY ? 0.f : c1 * SC;
    const float n0 = dead ? -INFINITY : -u0, n1 = dead ? -INFINITY : -u1;
    float f0, f1;
    if (T > 0) f0 = ex2(fmaf(a.m0, SC, -u0)), f1 = ex2(fmaf(a.m1, SC, -u1));
    a.m0 = c0;
    a.m1 = c1;
#pragma unroll
    for (int i = 0; i < 32; i++) s[i] = ex2(fmaf(s[i], SC, (i & 2) ? n1 : n0));
    if (T > 0) {
      pin(s);
      wg_wait<1>();
      pin(a.o);
#pragma unroll
      for (int i = 0; i < 20; i++) a.o[i] *= (i & 2) ? f1 : f0;
    }
    if (elect()) mbar_arrive(kvempty + 8 * (T & 1));
#pragma unroll
    for (int i = 0; i < 16; i++) a.p[i] = pack2(s[2 * i], s[2 * i + 1]);
  }
  if (T == 5) {
    const float i0 = rcp(a.o[16]), i1 = rcp(a.o[18]);
    const int lane = lane_id();
    const uint32_t oa = sb + STG_OFF + e.w * 8192 + (16 * wi + (lane & 15)) * 64 + (((lane >> 4) ^ ((lane & 7) >> 1)) << 4);
    named_bar(BAR_WG + e.w, 128);
#pragma unroll
    for (int i = 0; i < 2; i++)
      stsm4(oa ^ (i << 5), pack2(a.o[8 * i] * i0, a.o[8 * i + 1] * i0), pack2(a.o[8 * i + 2] * i1, a.o[8 * i + 3] * i1),
            pack2(a.o[8 * i + 4] * i0, a.o[8 * i + 5] * i0), pack2(a.o[8 * i + 6] * i1, a.o[8 * i + 7] * i1));
    stage_full(e);
  }
  if constexpr (T < 5) att_steps<T + 1>(acc, a, e, h, nb, sb, e0, e1, ph, da, db, wi, ready);
}

__global__ void __cluster_dims__(2, 1, 1) __launch_bounds__(NTHREADS, 1)
    fused_kernel(const __grid_constant__ Maps maps, const __nv_bfloat16* __restrict__ x, __nv_bfloat16* __restrict__ out) {
  extern __shared__ __align__(1024) uint8_t smem[];
  const uint32_t sb = (uint32_t)__cvta_generic_to_shared(smem);
  const int tid = threadIdx.x;
  const int warp = __shfl_sync(0xffffffffu, tid >> 5, 0);
  const int rank = blockIdx.x & 1, cl = blockIdx.x >> 1;
  const int m = 2 * (cl & 7) + rank, j = cl >> 3;
  const uint32_t fullb = sb + BAR_OFF, emptyb = fullb + 8 * STAGES;
  Flags* fl = &g_flags;

  if (tid == 0) {
#pragma unroll
    for (int i = 0; i < 21; i++) mbar_init(fullb + 8 * i, (i >> 2) == 1 ? 16 : ((i >> 1) == 5 ? 8 : 1));
    asm volatile("fence.mbarrier_init.release.cluster;" ::: "memory");
  }
  __syncwarp();
  cluster_arrive_relaxed();

  if (warp < 4) {
    asm volatile("setmaxnreg.dec.sync.aligned.u32 40;");
    const int lane = lane_id();
    cluster_wait();
    if (warp == 0) {
      uint32_t ph = 1;
      const int arow = m * 128;
#pragma unroll 1
      for (int wv = 0; wv < 5; wv++) {
        const int n = 8 * wv + j;
        const CUtensorMap* bm;
        int bc;
        if (wv == 0) {
          bm = &maps.wqkv;
          bc = (rank * 1024 + j * 128) >> 6;
        } else if (n < 12) {
          bm = &maps.wqkv;
          bc = (2048 + j * 256 + rank * 128) >> 6;
        } else {
          bm = rank ? &maps.wu : &maps.wg;
          bc = (n - 12) * 2;
        }
        const int swp = wv ? CS_AT : (m & 14);
        if (wv == 1) {
          mbar_wait(fullb + 144, 0);
          fence_async_all();
        }
#pragma unroll 1
        for (int ks = 0; ks < 16; ks++) {
          const int s = ks & 3;
          mbar_wait(emptyb + 8 * s, ph);
          if (elect()) {
            const int kp = ks & 14, k0 = (ks ^ ((kp == CS_AT || kp == swp) ? swp ^ CS_AT : 0)) * 64;
            mbar_expect_tx(fullb + 8 * s, STAGE_BYTES);
            tma_ld3_mc(sb + s * STAGE_BYTES + A_BYTES + rank * 16384, bm, k0, bc, fullb + 8 * s);
            tma_ld2(sb + s * STAGE_BYTES, wv ? &maps.xn : &maps.xr, k0, arow, fullb + 8 * s);
          }
          if (s == 3) ph ^= 1;
        }
      }
      const int kh = j >> 2, bc = ((j & 3) * 256 + rank * 128) >> 6;
#pragma unroll 1
      for (int ks = 0; ks < 36; ks++) {
        if (ks == 0 || ks == 20 || ks == 32) {
          mbar_wait(fullb + 120 + 8 * (ks >> 4), 0);
          fence_async_all();
        }
        const int s = ks & 3;
        const int k0 = g2_slice(kh, ks) * 64;
        mbar_wait(emptyb + 8 * s, ph);
        if (elect()) {
          mbar_expect_tx(fullb + 8 * s, STAGE_BYTES);
          tma_ld3_mc(sb + s * STAGE_BYTES + A_BYTES + rank * 16384, k0 < FF ? &maps.wd : &maps.wo,
                     k0 < FF ? k0 : k0 - FF, bc, fullb + 8 * s);
          tma_ld2_last(sb + s * STAGE_BYTES, &maps.hc_ld, k0, arow, fullb + 8 * s);
        }
        if (s == 3) ph ^= 1;
      }
      if (elect()) {
#pragma unroll 1
        for (int i = 0; i < 256; i += 64)
          asm volatile("cp.async.bulk.prefetch.tensor.2d.L2.global.tile [%0, {%1, %2}];" ::"l"(&maps.out),
                       "r"((j & 3) * 256 + i), "r"(arow + kh * 64)
                       : "memory");
      }
    } else if (warp < 3) {
      const int w = warp - 1;
      const uint32_t stg = sb + STG_OFF + w * 8192;
      const int row0 = m * 128 + w * 64;
      named_arrive(BAR_FREE + w, 160);
#pragma unroll 1
      for (int wv = 0; wv < 5; wv++) {
        const int n = 8 * wv + j;
        const bool kv = n < 12;
        const int nr = (wv == 1 && kv) ? 4 : 2;
        const int col = wv == 0 ? j * 128 : (kv ? 1024 + j * 256 : (n - 12) * 128);
        if (wv == 2) {
          mbar_wait(fullb + 112, 0);
          fence_async_all();
        }
#pragma unroll 1
        for (int r = 0; r < nr; r++) {
          named_bar(BAR_READY + w, 160);
          if (elect()) {
            tma_st2(kv ? &maps.kv_st : &maps.hc_st, col + 64 * r, row0, stg);
            bulk_commit();
            bulk_wait_read();
          }
          __syncwarp();
          if (wv < 2 || r == 0) named_arrive(BAR_FREE + w, 160);
        }
        int fi = n;
        if (wv >= 2) {
#pragma unroll 1
          for (int h = wv - 2; h < (wv == 4 ? 4 : wv - 1); h++) {
            if (elect()) {
              const int krow = m * 128 - 256 + w * 320;
              mbar_expect_tx(fullb + 96 + 8 * w, 8192);
              tma_ld2(stg, &maps.kv_ld, j * 128 + h * 32, krow, fullb + 96 + 8 * w);
              tma_ld2(stg + 4096, &maps.kv_ld, 1024 + j * 128 + h * 32, krow, fullb + 96 + 8 * w);
              if (fi >= 0) {
                bulk_wait_all();
                fence_async_all();
                flag_add(&fl->tile[m * 64 + fi]);
              }
            }
            __syncwarp();
            named_bar(BAR_READY + w, 160);
            if (elect()) {
              tma_st2(&maps.o_st, FF + j * 128 + h * 32, row0, stg);
              bulk_commit();
              bulk_wait_read();
            }
            __syncwarp();
            if (h < 2) named_arrive(BAR_FREE + w, 160);
            fi = (h & 1) ? 36 + 4 * h + j : -1;
          }
        }
        if (fi >= 0 && elect()) {
          bulk_wait_all();
          fence_async_all();
          flag_add(&fl->tile[m * 64 + fi]);
        }
        __syncwarp();
      }
#pragma unroll 1
      for (int p = 0; p < 4; p++) {
        named_bar(BAR_LN + 2 * p + w, 160);
        if (elect()) tma_red2(&maps.out, (j & 3) * 256 + p * 64, row0, sb + w * 8192 + p * STAGE_BYTES);
        __syncwarp();
      }
      int last = 0;
      if (elect()) {
        bulk_commit();
        last = atomicAdd(&fl->done[0], 1u) == 2 * NCTA - 1;
      }
      if (__any_sync(0xffffffffu, last)) {
#pragma unroll 1
        for (int i = lane; i < (int)(sizeof(Flags) / 16); i += 32) reinterpret_cast<uint4*>(fl)[i] = make_uint4(0, 0, 0, 0);
      }
      if (elect()) {
        bulk_wait_read();
      }
    } else {
#pragma unroll
      for (int i = 0; i < 2; i++)
        asm volatile("st.shared.v4.u32 [%0], {%1, %1, %1, %1};" ::"r"(sb + ONES_OFF + i * 512 + lane * 16), "r"(0x3f803f80u)
                     : "memory");
      fence_async_smem();
      {
        const int row0 = m * 128 + j * 16;
        mbar_wait<4>(fullb, 0);
        if (elect()) {
          mbar_expect_tx(fullb + 152, 32768);
          bulk_ld(sb + STG_OFF, x + row0 * DM, 32768, fullb + 152);
          mbar_wait(fullb + 152, 0);
          bulk_st(out + row0 * DM, sb + STG_OFF, 32768);
          bulk_commit();
          bulk_wait_read();
          mbar_arrive(fullb + 160);
        }
        __syncwarp();
#pragma unroll 1
        for (int i = 0; i < 3; i++) {
          named_bar(BAR_LN + i, 288);
          if (elect()) {
            if (i < 2) {
              bulk_st(g_xn + (row0 + 8 * i) * DM, sb + STG_OFF + i * 16384, 16384);
              bulk_st(g_st + row0 + 8 * i, fullb + 256 + 64 * i, 64);
            } else {
              uint32_t* dst = g_cs + (m & 14) * DM + j * 128 + rank * 64;
              bulk_st(dst, fullb + 512, 256);
              bulk_st(dst + DM, fullb + 768, 256);
            }
            bulk_commit();
            if (i == 2) {
              bulk_wait_all();
              fence_async_all();
              asm volatile("fence.acq_rel.gpu;\nred.relaxed.gpu.global.add.u32 [%0], 1;\nred.relaxed.gpu.global.add.u32 [%1], 1;" ::"l"(
                               &fl->ln[m * 32]),
                           "l"(&fl->cs[j * 32])
                           : "memory");
            }
          }
          __syncwarp();
        }
        const unsigned* p = lane ? &fl->cs[j * 32] : &fl->ln[m * 32];
        warp_poll(lane < 2 ? p : nullptr, 8 << lane);
        if (elect()) {
          mbar_expect_tx(fullb + 144, 8192 + 1024);
          tma_ld3_mc(sb + KV_OFF + rank * 4096, &maps.cs, 0, 4 * j + 2 * rank, fullb + 144);
          bulk_ld(sb + KV_OFF + 8192, g_st + m * 128, 1024, fullb + 144);
        }
        __syncwarp();
      }
      {
        const int mm = m - (lane & 3);
        warp_poll(lane < 8 && (lane & 3) < 3 && mm >= 0 ? &fl->tile[mm * 64 + (lane < 4 ? j : 8 + (j >> 1))] : nullptr, 2);
        if (elect()) mbar_arrive(fullb + 112);
      }
      const uint32_t kvfull = fullb + 64, kvempty = fullb + 80;
#pragma unroll 1
      for (int h = 0; h < 4; h++) {
#pragma unroll 1
        for (int i = 0; i < 5; i++) {
          const int b = i & 1;
          mbar_wait(kvempty + 8 * b, (b ? (i >> 1) : (h + (i >> 1))) & 1 ^ 1);
          if (elect()) {
            const uint32_t dst = sb + KV_OFF + b * 8192;
            const int krow = m * 128 - 256 + i * 64;
            mbar_expect_tx(kvfull + 8 * b, (i == 0 || i == 4) ? 4096 : 8192);
            if (i < 4) tma_ld2(dst, &maps.kv_ld, j * 128 + h * 32, krow + 64, kvfull + 8 * b);
            if (i > 0) tma_ld2(dst + 4096, &maps.kv_ld, 1024 + j * 128 + h * 32, krow, kvfull + 8 * b);
          }
          __syncwarp();
        }
        if (h > 0) {
          const int kh = j >> 2;
          const unsigned* p = nullptr;
          if (lane < (h == 1 ? 10 : 16 - 4 * h))
            p = &fl->tile[m * 64 + (h == 1 ? 12 + 10 * kh + lane : 16 * h + 4 * kh + (lane & 3) + 2 * (lane & 4))];
          warp_poll(p, 2);
          if (elect()) mbar_arrive(fullb + 112 + 8 * h);
        }
      }
    }
    __syncwarp();
    cluster_arrive_relaxed();
    cluster_wait();
  } else {
    asm volatile("setmaxnreg.inc.sync.aligned.u32 232;");
    const int w = (warp >> 2) - 1, wi = warp & 3, ct = tid - 128, lane = tid & 31;
    float acc[128];
    uint32_t pk[64];
    Epi e;
    cluster_wait();
    const uint32_t lane_off =
        (16 * wi + (lane & 7) + ((lane >> 3) & 1) * 8) * 128 + (((lane >> 4) ^ (lane & 7)) << 4);
    e.sta = sb + STG_OFF + w * 8192 + lane_off;
    e.qptr = g_q + blockIdx.x * 2048 + ct;
    e.w = w;
    const uint32_t e0 = mapa(emptyb, 0), e1 = mapa(emptyb, 1);
    const uint32_t da = make_desc(sb + w * 8192, 16);
    const uint32_t db = make_desc(sb + A_BYTES, 8192);
    uint32_t ph = 0;
    int type = P_QK;

    const int nb = 4 - 2 * m;
#pragma unroll 1
    for (int tile = 0; tile < 6; tile++) {
      Att a;
      int h = tile - 3;
      a.qa = a.qb = make_uint4(0, 0, 0, 0);
      if (tile > 0) {
        steps<0, 6, true>(acc, pk, e, type, fullb, e0, e1, ph, da, db);
        if (h >= 0) {
          a.qa = ld_q(e.qptr + 2 * h * 256);
          a.qb = ld_q(e.qptr + (2 * h + 1) * 256);
        }
        steps<6, 8, true>(acc, pk, e, type, fullb, e0, e1, ph, da, db);
      }
      do {
        int n = tile ? 7 : 15, st = 0;
        float cs[4] = {0.f, 0.f, 0.f, 0.f};
        if (h >= 0) {
          att_steps<0>(acc, a, e, h, nb, sb, e0, e1, ph, da, db, wi, false);
          n = h == 3 ? 13 : (h == 2 ? 2 : 1);
          st = 2;
          if (h == 2) {
            a.qa = ld_q(e.qptr + 6 * 256);
            a.qb = ld_q(e.qptr + 7 * 256);
          }
        }
        const int hold = (h == 3 && w == 1) ? SKN : 0;
#pragma unroll 1
        for (; n > 0; n--) {
          if (n == hold) named_bar(BAR_SKEW, 256);
          mbar_wait(fullb + 8 * st, ph);
          wg_fence();
#pragma unroll
          for (int kk = 0; kk < 4; kk++)
            wgmma_ss_n256_tb(acc, da + st * (STAGE_BYTES >> 4) + kk * 2, db + st * (STAGE_BYTES >> 4) + kk * 128,
                             kk > 0 || n != 15);
          wg_commit();
          wg_wait<1>();
          if (n != 15) release_stage(e0, e1, (st + 3) & 3);
          if (tile == 0) {
            int job = n == 15 - (w ? LN_B0 : LN_A0) ? 0 : (n == 15 - (w ? LN_B1 : LN_A1) ? 1 : -1);
            if (job >= 0) {
              ln_row(sb, job * 8 + w * 4 + wi);
              fence_async_smem();
              named_arrive(BAR_LN + job, 288);
            }
            if (n == 15 - CS_AT || n == 14 - CS_AT)
              colsum(cs, sb + st * STAGE_BYTES + A_BYTES + rank * 16384, fullb + 512, w * 4 + wi, n == 14 - CS_AT);
          }
          st = (st + 1) & 3;
          if (st == 0) ph ^= 1;
        }
      } while (++h == 3);
      mbar_wait(fullb + 24, ph);
      ph ^= 1;
      wg_fence();
#pragma unroll
      for (int kk = 0; kk < 4; kk++) {
        wgmma_ss_n256_tb(acc, da + 3 * (STAGE_BYTES >> 4) + kk * 2, db + 3 * (STAGE_BYTES >> 4) + kk * 128, 1);
      }
      wg_commit();
      if (tile == 5 && w == 0) named_arrive(BAR_SKEW, 256);
      wg_wait<1>();
      release_stage(e0, e1, 2);
      float i0 = 1.f, i1 = 1.f;
      if (tile == 0) {
        const uint32_t sta = sb + KV_OFF + 8192 + (w * 64 + wi * 16 + (lane_id() >> 2)) * 8;
        uint32_t a0, a1, a2, a3;
        mbar_wait(fullb + 144, 0);
        asm volatile(
            "ld.shared.u32 %0, [%6];\nld.shared.u32 %1, [%6 + 64];\nld.shared.u32 %2, [%6];\nld.shared.u32 %3, [%6 + 64];\n"
            "ld.shared.f32 %4, [%6 + 4];\nld.shared.f32 %5, [%6 + 68];"
            : "=r"(a0), "=r"(a1), "=r"(a2), "=r"(a3), "=f"(i0), "=f"(i1)
            : "r"(sta)
            : "memory");
        wg_fence();
        wgmma_rs_n256_tb(acc, a0, a1, a2, a3, make_desc(sb + KV_OFF, 2048), 1);
        wg_commit();
        wg_wait<0>();
      }
      wg_wait<0>();
      pin(acc);
      release_stage(e0, e1, 3);
      if (tile == 0) {
#pragma unroll
        for (int i = 0; i < 128; i++) acc[i] *= (i & 2) ? i1 : i0;
      }
#pragma unroll
      for (int i = 0; i < 64; i++) pk[i] = pack2(acc[2 * i], acc[2 * i + 1]);
      type = tile == 0 ? P_QK : ((tile == 1 && j < 4) ? P_V : P_GU);
    }
#pragma unroll
    for (int i = 0; i < 16; i++) {
      stsm4(((e.sta - STG_OFF) ^ ((i & 3) << 5)) + (i >> 2) * STAGE_BYTES, pk[4 * i], pk[4 * i + 1], pk[4 * i + 2],
            pk[4 * i + 3]);
      if ((i & 3) == 3) {
        fence_async_smem();
        named_arrive(BAR_LN + 2 * (i >> 2) + w, 160);
      }
    }
    __syncwarp();
    cluster_arrive_relaxed();
    cluster_wait();
  }
}

typedef CUresult (*EncodeFn)(CUtensorMap*, CUtensorMapDataType, cuuint32_t, void*, const cuuint64_t*, const cuuint64_t*,
                             const cuuint32_t*, const cuuint32_t*, CUtensorMapInterleave, CUtensorMapSwizzle,
                             CUtensorMapL2promotion, CUtensorMapFloatOOBfill);

static void map2d(EncodeFn enc, CUtensorMap* mp, const void* p, int cols, int rows, int box_rows, int box_cols = 64) {
  cuuint64_t dims[2] = {(cuuint64_t)cols, (cuuint64_t)rows};
  cuuint64_t strides[1] = {(cuuint64_t)cols * 2};
  cuuint32_t box[2] = {(cuuint32_t)box_cols, (cuuint32_t)box_rows};
  cuuint32_t es[2] = {1, 1};
  enc(mp, CU_TENSOR_MAP_DATA_TYPE_BFLOAT16, 2, const_cast<void*>(p), dims, strides, box, es,
      CU_TENSOR_MAP_INTERLEAVE_NONE, box_cols == 64 ? CU_TENSOR_MAP_SWIZZLE_128B : CU_TENSOR_MAP_SWIZZLE_64B,
      box_cols == 64 ? CU_TENSOR_MAP_L2_PROMOTION_L2_128B : CU_TENSOR_MAP_L2_PROMOTION_L2_64B,
      CU_TENSOR_MAP_FLOAT_OOB_FILL_NONE);
}
static void map3d(EncodeFn enc, CUtensorMap* mp, const void* p, int cols, int rows, int box_rows = 64) {
  cuuint64_t dims[3] = {64, (cuuint64_t)rows, (cuuint64_t)(cols / 64)};
  cuuint64_t strides[2] = {(cuuint64_t)cols * 2, 128};
  cuuint32_t box[3] = {64, (cuuint32_t)box_rows, 2};
  cuuint32_t es[3] = {1, 1, 1};
  enc(mp, CU_TENSOR_MAP_DATA_TYPE_BFLOAT16, 3, const_cast<void*>(p), dims, strides, box, es,
      CU_TENSOR_MAP_INTERLEAVE_NONE, CU_TENSOR_MAP_SWIZZLE_128B, CU_TENSOR_MAP_L2_PROMOTION_L2_256B,
      CU_TENSOR_MAP_FLOAT_OOB_FILL_NONE);
}

}

extern "C" void kernel_launch(void* const* d_in, const int* in_sizes, int n_in, void* d_out, int out_size) {
  using namespace fk;
  (void)in_sizes; (void)n_in; (void)out_size;
  static EncodeFn enc = nullptr;
  static void *xn, *kv, *hc, *cs;
  if (!enc) {
    void* fn = nullptr;
    cudaDriverEntryPointQueryResult qr;
    cudaGetDriverEntryPoint("cuTensorMapEncodeTiled", &fn, cudaEnableDefault, &qr);
    enc = (EncodeFn)fn;
    cudaGetSymbolAddress(&xn, g_xn);
    cudaGetSymbolAddress(&kv, g_kv);
    cudaGetSymbolAddress(&hc, g_hc);
    cudaGetSymbolAddress(&cs, g_cs);
    cudaFuncSetAttribute(fused_kernel, cudaFuncAttributeMaxDynamicSharedMemorySize, SMEM_BYTES);
  }
  Maps maps;
  map2d(enc, &maps.xr, d_in[0], DM, SEQ, 128);
  map3d(enc, &maps.cs, cs, 2 * DM, 16, 16);
  map2d(enc, &maps.xn, xn, DM, SEQ, 128);
  map3d(enc, &maps.wqkv, d_in[1], 3 * DM, DM);
  map3d(enc, &maps.wo, d_in[2], DM, DM);
  map3d(enc, &maps.wg, d_in[4], FF, DM);
  map3d(enc, &maps.wu, d_in[5], FF, DM);
  map3d(enc, &maps.wd, d_in[6], DM, FF);
  map2d(enc, &maps.kv_st, kv, 2 * DM, SEQ, 64);
  map2d(enc, &maps.kv_ld, kv, 2 * DM, SEQ, 64, 32);
  map2d(enc, &maps.hc_st, hc, KC, SEQ, 64);
  map2d(enc, &maps.hc_ld, hc, KC, SEQ, 128);
  map2d(enc, &maps.o_st, hc, KC, SEQ, 64, 32);
  map2d(enc, &maps.out, d_out, DM, SEQ, 64);
  fused_kernel<<<NCTA, NTHREADS, SMEM_BYTES>>>(maps, (const __nv_bfloat16*)d_in[0], (__nv_bfloat16*)d_out);
}
```
